```python
import torch

def _softmax(x, axis=-1):
    return torch.softmax(x, dim=axis)

def _gelu(x):
    return torch.nn.functional.gelu(x, approximate='tanh')

def _silu(x):
    return torch.nn.functional.silu(x)

def _sigmoid(x):
    return torch.sigmoid(x)

def _layernorm(x, axis=-1, eps=1e-05):
    m = x.mean(dim=axis, keepdim=True)
    v = x.var(dim=axis, keepdim=True, unbiased=False)
    return (x - m) / torch.sqrt(v + eps)

def _scatter_add(tgt, idx, src, axis=0):
    return tgt.clone().index_add_(axis, idx, src)

def _segment_sum(src, seg, n):
    out = torch.zeros((n,) + src.shape[1:], dtype=src.dtype)
    return out.index_add_(0, seg, src)

def _pad(x, pw):
    flat = tuple((v for pair in reversed(pw) for v in pair))
    return torch.nn.functional.pad(x, flat)
kernel_name = 'gated_mix__memory_aug_recurrent_mem_tr__swiglu_ffn__prompt'

def setup_inputs():

    _w = lambda a: (lambda t: t.to(torch.bfloat16) if t.is_floating_point() else t)(torch.as_tensor(a))

    def _A_setup():
        B, S, Dm = (1, 2048, 512)
        H, Dh = (32, 128)
        M, seg = (8, 32)
        seg = min(seg, S)
        S = S // seg * seg
        return {'x': _w((lambda *s: torch.randn(*s, dtype=torch.bfloat16) * 0.05)(B, S, Dm)), 'mem0': _w((lambda *s: torch.randn(*s, dtype=torch.bfloat16) * 0.4)(B, M, Dm)), 'Wq': _w((lambda *s: torch.randn(*s, dtype=torch.bfloat16) * 6.4)(Dm, H, Dh) * Dm ** (-0.5)), 'Wk': _w((lambda *s: torch.randn(*s, dtype=torch.bfloat16) * 6.4)(Dm, H, Dh) * Dm ** (-0.5)), 'Wv': _w((lambda *s: torch.randn(*s, dtype=torch.bfloat16) * 0.4)(Dm, H, Dh) * Dm ** (-0.5)), 'Wo': _w((lambda *s: torch.randn(*s, dtype=torch.bfloat16) * 0.4)(H, Dh, Dm) * (H * Dh) ** (-0.5)), 'seg_len': seg}
    _A_in = _A_setup()

    def _B_setup():
        B, S, D, F = (1, 2048, 512, 1376)
        return {'x': _w((lambda *s: torch.randn(*s, dtype=torch.bfloat16) * 0.05)(B, S, D)), 'w_gate': _w((lambda *s: torch.randn(*s, dtype=torch.bfloat16) * 0.05)(D, F)), 'w_up': _w((lambda *s: torch.randn(*s, dtype=torch.bfloat16) * 0.05)(D, F)), 'w_down': _w((lambda *s: torch.randn(*s, dtype=torch.bfloat16) * 0.05)(F, D))}
    _B_in = _B_setup()
    return {'A_x': _A_in['x'], 'A_mem0': _A_in['mem0'], 'A_Wq': _A_in['Wq'], 'A_Wk': _A_in['Wk'], 'A_Wv': _A_in['Wv'], 'A_Wo': _A_in['Wo'], 'A_seg_len': _A_in['seg_len'], 'B_x': _B_in['x'], 'B_w_gate': _B_in['w_gate'], 'B_w_up': _B_in['w_up'], 'B_w_down': _B_in['w_down'], 'gate_w': _w((lambda *s: torch.randn(*s, dtype=torch.bfloat16) * 0.05)(512) * 16.0)}

def reference(A_x, A_mem0, A_Wq, A_Wk, A_Wv, A_Wo, A_seg_len, B_x, B_w_gate, B_w_up, B_w_down, gate_w):

    def _A_ref(x, mem0, Wq, Wk, Wv, Wo, seg_len):
        B, S, Dm = x.shape
        H, Dh = (Wq.shape[1], Wq.shape[2])
        M = mem0.shape[1]
        scale = Dh ** (-0.5)
        n_seg = S // seg_len
        L = M + seg_len
        idx = torch.arange(L)
        mask = (idx[:, None] < M) | (idx[:, None] >= idx[None, :])
        mem = mem0
        outs = []
        for s in range(n_seg):
            xs = x[:, s * seg_len:(s + 1) * seg_len, :].clone()
            h = torch.concatenate([mem, xs], axis=1)
            q = torch.einsum('btd,dhe->bhte', h, Wq)
            k = torch.einsum('btd,dhe->bhte', h, Wk)
            v = torch.einsum('btd,dhe->bhte', h, Wv)
            scores = torch.einsum('bhqe,bhke->bhqk', q, k) * scale
            scores = torch.where(mask[None, None], scores, -1000000000.0)
            p = _softmax(scores, axis=-1)
            o = torch.einsum('bhqk,bhke->bhqe', p, v)
            o = torch.einsum('bhte,hed->btd', o, Wo)
            mem = o[:, :M, :].clone()
            outs.append(o[:, M:, :])
        return torch.concatenate(outs, axis=1)

    def _B_ref(x, w_gate, w_up, w_down):
        g = _silu(x @ w_gate)
        u = x @ w_up
        return g * u @ w_down
    x = A_x
    g = _sigmoid((x * gate_w).sum(-1, keepdims=True))
    a = _A_ref(x, A_mem0, A_Wq, A_Wk, A_Wv, A_Wo, A_seg_len)
    b = _B_ref(x, B_w_gate, B_w_up, B_w_down)
    return g * a + (1 - g) * b
```

```cpp
#include <cuda_runtime.h>
#include <cuda_bf16.h>
#include <cuda.h>
#include <stdint.h>

typedef __nv_bfloat16 bf16;
#define FSIDE 2
#define TCONST 0
#define TQUAL __device__ const
#define HINT 29
#define DEFI __device__ __forceinline__

constexpr int NSEG = 64, DM = 512, S = 2048, OHW = 5504;

__device__ __align__(1024) bf16 g_kv[S * 8192];
__device__ __align__(1024) bf16 g_oh[S * OHW];
__device__ __align__(1024) bf16 g_kvm[NSEG * 8 * 8192];
constexpr int MAXP = 33;
__device__ __align__(1024) uint4 g_part[32 * MAXP * 4096];
__device__ __align__(256) float g_gate[S];
__device__ __align__(1024) uint8_t g_win[1 << 20];
DEFI char* win_base() { return (char*)(((uintptr_t)g_win + 524287) & ~(uintptr_t)524287); }
constexpr int F_KV = 0, F_O = 1024, F_H = 1536, F_OT = 1552, F_P = 1568, F_C = 1600, F_P2 = 1664, F_Q = 1856, F_TK = 1857, F_EXIT = 1888, F_G = 1920, F_N = 2048;
__device__ uint32_t g_tk;
DEFI uint32_t* flags_base(uint32_t side) { return (uint32_t*)(win_base() + 262144 + 16384 + (FSIDE == 2 ? side * 8192 : side ^ FSIDE ? 12288 : 4096)); }
#define TP(i)

constexpr int T_KV = 0, T_F = 1, T_QA = 2, T_OP = 3, T_OF = 4, T_RD = 5, T_AO = 6, T_EXIT = 7;
constexpr uint32_t NIND = 352, NEX = 726, NFB = 662, NFOL = 128, NTASK = 918;
constexpr unsigned long long OPF_GROUPS = 0xa49224924924ull;
TQUAL uint32_t g_tasks[NTASK] = {
  0x4000, 0x4080, 0x4100, 0x4180, 0x4200, 0x4280, 0x4300, 0x4380, 0x4400, 0x4480, 0x4500, 0x4580,
  0x4600, 0x4680, 0x4700, 0x4780, 0x4800, 0x4880, 0x4900, 0x4980, 0x4a00, 0x4a80, 0x4b00, 0x4b80,
  0x4c00, 0x4c80, 0x4d00, 0x4d80, 0x4e00, 0x4e80, 0x4f00, 0x4f80, 0x5000, 0x5080, 0x5100, 0x5180,
  0x5200, 0x5280, 0x5300, 0x5380, 0x5400, 0x5480, 0x5500, 0x5580, 0x5600, 0x5680, 0x5700, 0x5780,
  0x5800, 0x5880, 0x5900, 0x5980, 0x5a00, 0x5a80, 0x5b00, 0x5b80, 0x5c00, 0x5c80, 0x5d00, 0x5d80,
  0x5e00, 0x5e80, 0x5f00, 0x5f80, 0x4008, 0x4088, 0x4108, 0x4188, 0x4208, 0x4288, 0x4308, 0x4388,
  0x4408, 0x4488, 0x4508, 0x4588, 0x4608, 0x4688, 0x4708, 0x4788, 0x4808, 0x4888, 0x4908, 0x4988,
  0x4a08, 0x4a88, 0x4b08, 0x4b88, 0x4c08, 0x4c88, 0x4d08, 0x4d88, 0x4e08, 0x4e88, 0x4f08, 0x4f88,
  0x5008, 0x5088, 0x5108, 0x5188, 0x5208, 0x5288, 0x5308, 0x5388, 0x5408, 0x5488, 0x5508, 0x5588,
  0x5608, 0x5688, 0x5708, 0x5788, 0x5808, 0x5888, 0x5908, 0x5988, 0x5a08, 0x5a88, 0x5b08, 0x5b88,
  0x5c08, 0x5c88, 0x5d08, 0x5d88, 0x5e08, 0x5e88, 0x5f08, 0x5f88, 0x8010, 0x8110, 0x8210, 0x8310,
  0x8410, 0x8510, 0x8610, 0x8710, 0x8810, 0x8910, 0x8a10, 0x8b10, 0x8c10, 0x8d10, 0x8e10, 0x8f10,
  0x9010, 0x9110, 0x9210, 0x9310, 0x9410, 0x9510, 0x9610, 0x9710, 0x9810, 0x9910, 0x9a10, 0x9b10,
  0x9c10, 0x9d10, 0x9e10, 0x9f10, 0x10018, 0x10218, 0x10418, 0x10618, 0x10818, 0x10a18, 0x10c18, 0x10e18,
  0x11018, 0x11218, 0x11418, 0x11618, 0x11818, 0x11a18, 0x11c18, 0x11e18, 0x10020, 0x10220, 0x10420, 0x10620,
  0x10820, 0x10a20, 0x10c20, 0x10e20, 0x11020, 0x11220, 0x11420, 0x11620, 0x11820, 0x11a20, 0x11c20, 0x11e20,
  0x20028, 0x20428, 0x20828, 0x20c28, 0x21028, 0x21428, 0x21828, 0x21c28, 0x14001, 0x18281, 0x18581, 0x14881,
  0x20030, 0x20430, 0x20830, 0x20c30, 0x21030, 0x21430, 0x21830, 0x21c30, 0x14009, 0x18289, 0x18589, 0x14889,
  0x20038, 0x20438, 0x20838, 0x20c38, 0x21038, 0x21438, 0x21838, 0x21c38, 0x14011, 0x18291, 0x18591, 0x14891,
  0x20040, 0x20440, 0x20840, 0x20c40, 0x21040, 0x21440, 0x21840, 0x21c40, 0x14019, 0x18299, 0x18599, 0x14899,
  0x20048, 0x20448, 0x20848, 0x20c48, 0x21048, 0x21448, 0x21848, 0x21c48, 0x14021, 0x182a1, 0x185a1, 0x148a1,
  0x20050, 0x20450, 0x20850, 0x20c50, 0x21050, 0x21450, 0x21850, 0x21c50, 0x14029, 0x182a9, 0x185a9, 0x148a9,
  0x20058, 0x20458, 0x20858, 0x20c58, 0x21058, 0x21458, 0x21858, 0x21c58, 0x14031, 0x182b1, 0x185b1, 0x148b1,
  0x20060, 0x20460, 0x20860, 0x20c60, 0x21060, 0x21460, 0x21860, 0x21c60, 0x14039, 0x182b9, 0x185b9, 0x148b9,
  0x20068, 0x20468, 0x20868, 0x20c68, 0x21068, 0x21468, 0x21868, 0x21c68, 0x14041, 0x182c1, 0x185c1, 0x148c1,
  0x20070, 0x20470, 0x20870, 0x20c70, 0x21070, 0x21470, 0x21870, 0x21c70, 0x14049, 0x182c9, 0x185c9, 0x148c9,
  0x20078, 0x20478, 0x20878, 0x20c78, 0x21078, 0x21478, 0x21878, 0x21c78, 0x14051, 0x182d1, 0x185d1, 0x148d1,
  0x14059, 0x182d9, 0x185d9, 0x148d9, 0x14061, 0x182e1, 0x185e1, 0x148e1, 0x14069, 0x182e9, 0x185e9, 0x148e9,
  0x14071, 0x182f1, 0x185f1, 0x148f1, 0x14079, 0x182f9, 0x185f9, 0x148f9, 0x12078, 0x12278, 0x12478, 0x12678,
  0x12878, 0x12a78, 0x12c78, 0x12e78, 0x10002, 0x10202, 0x10402, 0x10602, 0x10802, 0x10a02, 0x10c02, 0x10e02,
  0x1000a, 0x1020a, 0x1040a, 0x1060a, 0x1080a, 0x10a0a, 0x10c0a, 0x10e0a, 0x5a003, 0x25a003, 0x470003, 0x670003,
  0x490e04, 0x690e04, 0x10012, 0x10212, 0x10412, 0x10612, 0x10812, 0x10a12, 0x10c12, 0x10e12, 0x5a00b, 0x25a00b,
  0x47000b, 0x67000b, 0x490e0c, 0x690e0c, 0x1001a, 0x1021a, 0x1041a, 0x1061a, 0x1081a, 0x10a1a, 0x10c1a, 0x10e1a,
  0x5a013, 0x25a013, 0x470013, 0x670013, 0x490e14, 0x690e14, 0x10022, 0x10222, 0x10422, 0x10622, 0x10822, 0x10a22,
  0x10c22, 0x10e22, 0x5a01b, 0x25a01b, 0x47001b, 0x67001b, 0x490e1c, 0x690e1c, 0x1002a, 0x1022a, 0x1042a, 0x1062a,
  0x1082a, 0x10a2a, 0x10c2a, 0x10e2a, 0x5a023, 0x25a023, 0x470023, 0x670023, 0x490e24, 0x690e24, 0x10032, 0x10232,
  0x10432, 0x10632, 0x10832, 0x10a32, 0x10c32, 0x10e32, 0x5a02b, 0x25a02b, 0x47002b, 0x67002b, 0x490e2c, 0x690e2c,
  0x1003a, 0x1023a, 0x1043a, 0x1063a, 0x1083a, 0x10a3a, 0x10c3a, 0x10e3a, 0x5a033, 0x25a033, 0x470033, 0x670033,
  0x490e34, 0x690e34, 0x10042, 0x10242, 0x10442, 0x10642, 0x10842, 0x10a42, 0x10c42, 0x10e42, 0x5a03b, 0x25a03b,
  0x47003b, 0x67003b, 0x490e3c, 0x690e3c, 0x1004a, 0x1024a, 0x1044a, 0x1064a, 0x1084a, 0x10a4a, 0x10c4a, 0x10e4a,
  0x5a043, 0x25a043, 0x470043, 0x670043, 0x490e44, 0x690e44, 0x8052, 0x8152, 0x8252, 0x8352, 0x8452, 0x8552,
  0x8652, 0x8752, 0x8852, 0x8952, 0x8a52, 0x8b52, 0x8c52, 0x8d52, 0x8e52, 0x8f52, 0x5a04b, 0x25a04b,
  0x45004b, 0x65004b, 0x850a4b, 0xa50a4b, 0x86144c, 0xa6144c, 0x805a, 0x815a, 0x825a, 0x835a, 0x845a, 0x855a,
  0x865a, 0x875a, 0x885a, 0x895a, 0x8a5a, 0x8b5a, 0x8c5a, 0x8d5a, 0x8e5a, 0x8f5a, 0x5a053, 0x25a053,
  0x450053, 0x650053, 0x850a53, 0xa50a53, 0x861454, 0xa61454, 0x8062, 0x8162, 0x8262, 0x8362, 0x8462, 0x8562,
  0x8662, 0x8762, 0x8862, 0x8962, 0x8a62, 0x8b62, 0x8c62, 0x8d62, 0x8e62, 0x8f62, 0x5a05b, 0x25a05b,
  0x45005b, 0x65005b, 0x850a5b, 0xa50a5b, 0x86145c, 0xa6145c, 0x406a, 0x40ea, 0x416a, 0x41ea, 0x426a, 0x42ea,
  0x436a, 0x43ea, 0x446a, 0x44ea, 0x456a, 0x45ea, 0x466a, 0x46ea, 0x476a, 0x47ea, 0x486a, 0x48ea,
  0x496a, 0x49ea, 0x4a6a, 0x4aea, 0x4b6a, 0x4bea, 0x4c6a, 0x4cea, 0x4d6a, 0x4dea, 0x4e6a, 0x4eea,
  0x4f6a, 0x4fea, 0x5a063, 0x25a063, 0x420063, 0x620063, 0x820463, 0xa20463, 0xc20863, 0xe20863, 0x1020c63, 0x1220c63,
  0x1421063, 0x1621063, 0x1821463, 0x1a21463, 0x1c21863, 0x1e21863, 0x2021c63, 0x2221c63, 0x4072, 0x40f2, 0x4172, 0x41f2,
  0x4272, 0x42f2, 0x4372, 0x43f2, 0x4472, 0x44f2, 0x4572, 0x45f2, 0x4672, 0x46f2, 0x4772, 0x47f2,
  0x4872, 0x48f2, 0x4972, 0x49f2, 0x4a72, 0x4af2, 0x4b72, 0x4bf2, 0x4c72, 0x4cf2, 0x4d72, 0x4df2,
  0x4e72, 0x4ef2, 0x4f72, 0x4ff2, 0x5a06b, 0x25a06b, 0x2008065, 0x2208065, 0x2008165, 0x2208165, 0x2008265, 0x2208265,
  0x2008365, 0x2208365, 0x2008465, 0x2208465, 0x2008565, 0x2208565, 0x2008665, 0x2208665, 0x2008765, 0x2208765, 0x5a073, 0x25a073,
  0x5a07b, 0x25a07b, 0x40807e, 0x60807e, 0x80817e, 0xa0817e, 0xc0827e, 0xe0827e, 0x100837e, 0x120837e, 0x140847e, 0x160847e,
  0x180857e, 0x1a0857e, 0x1c0867e, 0x1e0867e, 0x200877e, 0x220877e, 0x240887e, 0x260887e, 0x280897e, 0x2a0897e, 0x2c08a7e, 0x2e08a7e,
  0x3008b7e, 0x3208b7e, 0x3408c7e, 0x3608c7e, 0x3808d7e, 0x3a08d7e, 0x3c08e7e, 0x3e08e7e, 0x4008f7e, 0x4208f7e, 0x42006b, 0x62006b,
  0x82046b, 0xa2046b, 0xc2086b, 0xe2086b, 0x1020c6b, 0x1220c6b, 0x142106b, 0x162106b, 0x182146b, 0x1a2146b, 0x1c2186b, 0x1e2186b,
  0x2021c6b, 0x2221c6b, 0x420073, 0x620073, 0x820473, 0xa20473, 0xc20873, 0xe20873, 0x1020c73, 0x1220c73, 0x1421073, 0x1621073,
  0x1821473, 0x1a21473, 0x1c21873, 0x1e21873, 0x2021c73, 0x2221c73, 0x1040407e, 0x1060407e, 0x108040fe, 0x10a040fe, 0x10c0417e, 0x10e0417e,
  0x110041fe, 0x112041fe, 0x1140427e, 0x1160427e, 0x118042fe, 0x11a042fe, 0x11c0437e, 0x11e0437e, 0x120043fe, 0x122043fe, 0x1240447e, 0x1260447e,
  0x128044fe, 0x12a044fe, 0x12c0457e, 0x12e0457e, 0x130045fe, 0x132045fe, 0x1340467e, 0x1360467e, 0x138046fe, 0x13a046fe, 0x13c0477e, 0x13e0477e,
  0x140047fe, 0x142047fe, 0x1440487e, 0x1460487e, 0x148048fe, 0x14a048fe, 0x14c0497e, 0x14e0497e, 0x150049fe, 0x152049fe, 0x15404a7e, 0x15604a7e,
  0x15804afe, 0x15a04afe, 0x15c04b7e, 0x15e04b7e, 0x16004bfe, 0x16204bfe, 0x16404c7e, 0x16604c7e, 0x16804cfe, 0x16a04cfe, 0x16c04d7e, 0x16e04d7e,
  0x17004dfe, 0x17204dfe, 0x17404e7e, 0x17604e7e, 0x17804efe, 0x17a04efe, 0x17c04f7e, 0x17e04f7e, 0x18004ffe, 0x18204ffe, 0x2400807d, 0x2420807d,
  0x2400817d, 0x2420817d, 0x2400827d, 0x2420827d, 0x2400837d, 0x2420837d, 0x2400847d, 0x2420847d, 0x2400857d, 0x2420857d, 0x2400867d, 0x2420867d,
  0x2400877d, 0x2420877d, 0x2400887d, 0x2420887d, 0x2400897d, 0x2420897d, 0x24008a7d, 0x24208a7d, 0x24008b7d, 0x24208b7d, 0x24008c7d, 0x24208c7d,
  0x24008d7d, 0x24208d7d, 0x24008e7d, 0x24208e7d, 0x24008f7d, 0x24208f7d, 0x200806d, 0x220806d, 0x200816d, 0x220816d, 0x200826d, 0x220826d,
  0x200836d, 0x220836d, 0x200846d, 0x220846d, 0x200856d, 0x220856d, 0x200866d, 0x220866d, 0x200876d, 0x220876d, 0x2008075, 0x2208075,
  0x2008175, 0x2208175, 0x2008275, 0x2208275, 0x2008375, 0x2208375, 0x2008475, 0x2208475, 0x2008575, 0x2208575, 0x2008675, 0x2208675,
  0x2008775, 0x2208775, 0x3800407d, 0x3820407d, 0x380040fd, 0x382040fd, 0x3800417d, 0x3820417d, 0x380041fd, 0x382041fd, 0x3800427d, 0x3820427d,
  0x380042fd, 0x382042fd, 0x3800437d, 0x3820437d, 0x380043fd, 0x382043fd, 0x3800447d, 0x3820447d, 0x380044fd, 0x382044fd, 0x3800457d, 0x3820457d,
  0x380045fd, 0x382045fd, 0x3800467d, 0x3820467d, 0x380046fd, 0x382046fd, 0x3800477d, 0x3820477d, 0x380047fd, 0x382047fd, 0x3800487d, 0x3820487d,
  0x380048fd, 0x382048fd, 0x3800497d, 0x3820497d, 0x380049fd, 0x382049fd, 0x38004a7d, 0x38204a7d, 0x38004afd, 0x38204afd, 0x38004b7d, 0x38204b7d,
  0x38004bfd, 0x38204bfd, 0x38004c7d, 0x38204c7d, 0x38004cfd, 0x38204cfd, 0x38004d7d, 0x38204d7d, 0x38004dfd, 0x38204dfd, 0x38004e7d, 0x38204e7d,
  0x38004efd, 0x38204efd, 0x38004f7d, 0x38204f7d, 0x38004ffd, 0x38204ffd,
};
__device__ const uint32_t g_grp[128] = {
  0x40011d60, 0x40051d68, 0x2c0570, 0x10390d72, 0x40091d76, 0x12c057e, 0x11390d80, 0x400d1d84, 0x22c058c, 0x12390d8e,
  0x40111d92, 0x32c059a, 0x13390d9c, 0x40151da0, 0x42c05a8, 0x14390daa, 0x40191dae, 0x52c05b6, 0x15390db8, 0x401d1dbc,
  0x62c05c4, 0x16390dc6, 0x40211dca, 0x72c05d2, 0x17390dd4, 0x40251dd8, 0x82c05e0, 0x18390de2, 0x40293de6, 0x92c05f6,
  0x193915f8, 0x402d3dfe, 0x403c7e96, 0xa2c060e, 0x1a3d1610, 0x40313e16, 0xb2c0626, 0x1b3d1628, 0x40357e2e, 0xc2c064e,
  0x1c3d3e50, 0x40377e60, 0xd2c0680, 0x1d383eb6, 0x38123e82, 0xe2c0692, 0x403c3ec6, 0xf2c0694, 0x0, 0x0,
  0x0, 0x0, 0x0, 0x0, 0x0, 0x0, 0x0, 0x0, 0x0, 0x0,
  0x0, 0x0, 0x0, 0x0, 0x3f0080, 0x3f00a0, 0x3f0000, 0x20080, 0x3f00b0, 0x3f0000,
  0x500a0, 0x3f00c0, 0x3f0000, 0x800b0, 0x3f00c8, 0x3f0000, 0xb00c0, 0x3f00d4, 0x3f0000, 0xe00c8,
  0x3f00e0, 0x3f0000, 0x1100d4, 0x3f00ec, 0x3f0000, 0x1400e0, 0x3f00f8, 0x3f0000, 0x1700ec, 0x3f0104,
  0x3f0000, 0x1a00f8, 0x3f0110, 0x3f0000, 0x1d0104, 0x3f011c, 0x3e0160, 0x3f0000, 0x210110, 0x3f0128,
  0x3f0000, 0x24011c, 0x3f0134, 0x3f0000, 0x3f0128, 0x3f0140, 0x3f0000, 0x3e0160, 0x270128, 0x3f0000,
  0x3e0160, 0x3f0000, 0x3f0000, 0x3f0000, 0x3f0000, 0x3f0000, 0x3f0000, 0x3f0000, 0x3f0000, 0x3f0000,
  0x3f0000, 0x3f0000, 0x3f0000, 0x3f0000, 0x3f0000, 0x3f0000, 0x3f0000, 0x3f0000,
};

DEFI uint32_t smem_u32(const void* p) { return (uint32_t)__cvta_generic_to_shared(p); }
DEFI uint32_t mapa(uint32_t a, uint32_t r) { uint32_t o; asm("mapa.shared::cluster.u32 %0, %1, %2;" : "=r"(o) : "r"(a), "r"(r)); return o; }
DEFI void mbar_init(uint32_t a, uint32_t c) { asm volatile("mbarrier.init.shared::cta.b64 [%0], %1;" :: "r"(a), "r"(c) : "memory"); }
DEFI void mbar_expect(uint32_t a, uint32_t b) { asm volatile("mbarrier.arrive.expect_tx.shared::cta.b64 _, [%0], %1;" :: "r"(a), "r"(b) : "memory"); }
DEFI void mbar_spin(uint32_t a, uint32_t p) {
  asm volatile("{\n.reg .pred q;\nLW:\nmbarrier.try_wait.parity.shared::cta.b64 q, [%0], %1;\n@!q bra.uni LW;\n}" :: "r"(a), "r"(p) : "memory");
}
DEFI bool mbar_try(uint32_t a, uint32_t p) {
  uint32_t r; asm volatile("{\n.reg .pred q;\nmbarrier.try_wait.parity.shared::cta.b64 q, [%1], %2;\nselp.u32 %0, 1, 0, q;\n}" : "=r"(r) : "r"(a), "r"(p) : "memory"); return r;
}
DEFI void mbar_fin(bool p, uint32_t a, uint32_t ph) {
  asm volatile("{\n.reg .pred q;\nsetp.ne.u32 q, %2, 0;\n@q bra.uni LD;\nLW:\nmbarrier.try_wait.parity.shared::cta.b64 q, [%0], %1;\n@!q bra.uni LW;\nLD:\n}" :: "r"(a), "r"(ph), "r"((uint32_t)p) : "memory");
}
DEFI void arrive_tx_p(uint32_t a, uint32_t tx, bool p) {
  asm volatile("{\n.reg .pred q;\nsetp.ne.s32 q, %2, 0;\n@q mbarrier.arrive.expect_tx.shared::cta.b64 _, [%0], %1;\n}" :: "r"(a), "r"(tx), "r"((int)p) : "memory");
}
DEFI void arrive_tx_e(uint32_t a, uint32_t tx) {
  asm volatile("{\n.reg .pred q;\nelect.sync _|q, 0xffffffff;\n@q mbarrier.arrive.expect_tx.shared::cta.b64 _, [%0], %1;\n}" :: "r"(a), "r"(tx) : "memory");
}
DEFI void arrive_e(uint32_t a) {
  asm volatile("{\n.reg .pred q;\nelect.sync _|q, 0xffffffff;\n@q mbarrier.arrive.shared::cta.b64 _, [%0];\n}" :: "r"(a) : "memory");
}
DEFI void arrive2_p(uint32_t a, bool p) {
  asm volatile("{\n.reg .pred q;\nsetp.ne.s32 q, %1, 0;\n@q mbarrier.arrive.shared::cta.b64 _, [%0], 2;\n}" :: "r"(a), "r"((int)p) : "memory");
}
DEFI void arrive_p(uint32_t a, bool p) {
  asm volatile("{\n.reg .pred q;\nsetp.ne.s32 q, %1, 0;\n@q mbarrier.arrive.shared::cta.b64 _, [%0];\n}" :: "r"(a), "r"((int)p) : "memory");
}
DEFI void sfence(uint32_t z, uint32_t s) {
  asm volatile("{\n.reg .pred q;\n.reg .u32 t;\nsetp.ne.u32 q, %0, %1;\n@q bra.uni LD;\nLW:\nld.volatile.shared.u32 t, [%0];\nsetp.eq.u32 q, t, %1;\n@q bra.uni LW;\nLD:\n}" :: "r"(z), "r"(s) : "memory");
}
DEFI void bar_sync(int id, int n) { asm volatile("bar.sync %0, %1;" :: "r"(id), "r"(n) : "memory"); }
DEFI void bar_arrive(int id, int n) { asm volatile("bar.arrive %0, %1;" :: "r"(id), "r"(n) : "memory"); }
DEFI bool bar_and(int id, int n, bool p) {
  uint32_t r; asm volatile("{\n.reg .pred q;\nsetp.ne.u32 q, %3, 0;\nbar.red.and.pred q, %1, %2, q;\nselp.u32 %0, 1, 0, q;\n}" : "=r"(r) : "r"(id), "r"(n), "r"((uint32_t)p) : "memory"); return r;
}
DEFI void cluster_sync() { asm volatile("barrier.cluster.arrive.aligned; barrier.cluster.wait.aligned;" ::: "memory"); }
DEFI void fence_async_smem() { asm volatile("fence.proxy.async.shared::cta;" ::: "memory"); }
DEFI void st_async1(uint32_t a, uint32_t mb, uint32_t v) { asm volatile("st.async.weak.shared::cluster.mbarrier::complete_tx::bytes.b32 [%0], %2, [%1];" :: "r"(a), "r"(mb), "r"(v) : "memory"); }
DEFI void st_async2(uint32_t a, uint32_t mb, uint32_t x, uint32_t y) { asm volatile("st.async.weak.shared::cluster.mbarrier::complete_tx::bytes.v2.b32 [%0], {%2,%3}, [%1];" :: "r"(a), "r"(mb), "r"(x), "r"(y) : "memory"); }
DEFI void st_async4(uint32_t a, uint32_t mb, uint32_t x, uint32_t y, uint32_t z, uint32_t w) { asm volatile("st.async.weak.shared::cluster.mbarrier::complete_tx::bytes.v4.b32 [%0], {%2,%3,%4,%5}, [%1];" :: "r"(a), "r"(mb), "r"(x), "r"(y), "r"(z), "r"(w) : "memory"); }
DEFI void mma(float (&c)[4], const uint32_t (&a)[4], uint32_t b0, uint32_t b1) {
  asm volatile("mma.sync.aligned.m16n8k16.row.col.f32.bf16.bf16.f32 {%0,%1,%2,%3}, {%4,%5,%6,%7}, {%8,%9}, {%0,%1,%2,%3};"
    : "+f"(c[0]), "+f"(c[1]), "+f"(c[2]), "+f"(c[3]) : "r"(a[0]), "r"(a[1]), "r"(a[2]), "r"(a[3]), "r"(b0), "r"(b1));
}
DEFI void mmaz(float (&c)[4], const uint32_t (&a)[4], uint32_t b0, uint32_t b1) {
  asm volatile("mma.sync.aligned.m16n8k16.row.col.f32.bf16.bf16.f32 {%0,%1,%2,%3}, {%4,%5,%6,%7}, {%8,%9}, {%10,%10,%10,%10};"
    : "=f"(c[0]), "=f"(c[1]), "=f"(c[2]), "=f"(c[3]) : "r"(a[0]), "r"(a[1]), "r"(a[2]), "r"(a[3]), "r"(b0), "r"(b1), "f"(0.f));
}
DEFI void mma8(float (&c)[4], uint32_t a0, uint32_t a1, uint32_t b0) {
  asm volatile("mma.sync.aligned.m16n8k8.row.col.f32.bf16.bf16.f32 {%0,%1,%2,%3}, {%4,%5}, {%6}, {%0,%1,%2,%3};"
    : "+f"(c[0]), "+f"(c[1]), "+f"(c[2]), "+f"(c[3]) : "r"(a0), "r"(a1), "r"(b0));
}
DEFI void sts128f(uint32_t a, float x, float y, float z, float w) { asm volatile("st.shared.v4.f32 [%0], {%1,%2,%3,%4};" :: "r"(a), "f"(x), "f"(y), "f"(z), "f"(w) : "memory"); }
DEFI void ldsm4(uint32_t (&r)[4], uint32_t a) { asm volatile("ldmatrix.sync.aligned.m8n8.x4.shared.b16 {%0,%1,%2,%3}, [%4];" : "=r"(r[0]), "=r"(r[1]), "=r"(r[2]), "=r"(r[3]) : "r"(a) : "memory"); }
DEFI void ldsm4t(uint32_t (&r)[4], uint32_t a) { asm volatile("ldmatrix.sync.aligned.m8n8.x4.trans.shared.b16 {%0,%1,%2,%3}, [%4];" : "=r"(r[0]), "=r"(r[1]), "=r"(r[2]), "=r"(r[3]) : "r"(a) : "memory"); }
DEFI void stsm4(uint32_t a, uint32_t r0, uint32_t r1, uint32_t r2, uint32_t r3) { asm volatile("stmatrix.sync.aligned.m8n8.x4.shared.b16 [%0], {%1,%2,%3,%4};" :: "r"(a), "r"(r0), "r"(r1), "r"(r2), "r"(r3) : "memory"); }
DEFI void stsm4t(uint32_t a, uint32_t r0, uint32_t r1, uint32_t r2, uint32_t r3) { asm volatile("stmatrix.sync.aligned.m8n8.x4.trans.shared.b16 [%0], {%1,%2,%3,%4};" :: "r"(a), "r"(r0), "r"(r1), "r"(r2), "r"(r3) : "memory"); }
DEFI void lds128(uint32_t (&r)[4], uint32_t a) { asm volatile("ld.volatile.shared.v4.b32 {%0,%1,%2,%3}, [%4];" : "=r"(r[0]), "=r"(r[1]), "=r"(r[2]), "=r"(r[3]) : "r"(a) : "memory"); }
DEFI void sts128(uint32_t a, uint32_t x, uint32_t y, uint32_t z, uint32_t w) { asm volatile("st.shared.v4.b32 [%0], {%1,%2,%3,%4};" :: "r"(a), "r"(x), "r"(y), "r"(z), "r"(w) : "memory"); }
DEFI void lds64(uint32_t& x, uint32_t& y, uint32_t a) { asm volatile("ld.volatile.shared.v2.b32 {%0,%1}, [%2];" : "=r"(x), "=r"(y) : "r"(a) : "memory"); }
DEFI void lds64f(float& x, float& y, uint32_t a) { asm volatile("ld.volatile.shared.v2.f32 {%0,%1}, [%2];" : "=f"(x), "=f"(y) : "r"(a) : "memory"); }
DEFI void sts64(uint32_t a, uint32_t x, uint32_t y) { asm volatile("st.shared.v2.b32 [%0], {%1,%2};" :: "r"(a), "r"(x), "r"(y) : "memory"); }
DEFI void sts32(uint32_t a, uint32_t x) { asm volatile("st.shared.b32 [%0], %1;" :: "r"(a), "r"(x) : "memory"); }
DEFI uint32_t lds32(uint32_t a) { uint32_t x; asm volatile("ld.volatile.shared.b32 %0, [%1];" : "=r"(x) : "r"(a) : "memory"); return x; }
DEFI uint32_t pack(float lo, float hi) { uint32_t r; asm("cvt.rn.bf16x2.f32 %0, %1, %2;" : "=r"(r) : "f"(hi), "f"(lo)); return r; }
DEFI float blo(uint32_t w) { return __uint_as_float(w << 16); }
DEFI float bhi(uint32_t w) { return __uint_as_float(w & 0xFFFF0000u); }
DEFI uint32_t hadd2(uint32_t a, uint32_t b) { uint32_t r; asm("add.rn.bf16x2 %0, %1, %2;" : "=r"(r) : "r"(a), "r"(b)); return r; }
DEFI uint32_t movm(uint32_t a) { uint32_t r; asm volatile("movmatrix.sync.aligned.m8n8.trans.b16 %0, %1;" : "=r"(r) : "r"(a)); return r; }
DEFI float ex2(float x) { float r; asm("ex2.approx.ftz.f32 %0, %1;" : "=f"(r) : "f"(x)); return r; }
DEFI float rcpa(float x) { float r; asm("rcp.approx.ftz.f32 %0, %1;" : "=f"(r) : "f"(x)); return r; }
DEFI uint32_t clk() { uint32_t t; asm volatile("mov.u32 %0, %%clock;" : "=r"(t) :: "memory"); return t; }
DEFI uint32_t gtime() { uint32_t t; asm volatile("mov.u32 %0, %%globaltimer_lo;" : "=r"(t) :: "memory"); return t; }
DEFI uint32_t opq(uint32_t v) { return __shfl_sync(0xffffffffu, v, threadIdx.x & 31); }
DEFI bool uni(bool p) { return __all_sync(0xffffffffu, p); }
DEFI void tma2d(uint32_t dst, const CUtensorMap* m, uint32_t mb, int c0, int c1) {
  asm volatile("{\n.reg .pred q;\nelect.sync _|q, 0xffffffff;\n@q cp.async.bulk.tensor.2d.shared::cluster.global.mbarrier::complete_tx::bytes [%0], [%1, {%3, %4}], [%2];\n}"
    :: "r"(dst), "l"(m), "r"(mb), "r"(c0), "r"(c1) : "memory");
}
DEFI uint64_t pol_stream(bool on) {
  uint64_t a, b;
  asm("createpolicy.fractional.L2::evict_first.b64 %0, 1.0;" : "=l"(a));
  asm("createpolicy.fractional.L2::evict_normal.b64 %0, 1.0;" : "=l"(b));
  return on ? a : b;
}
DEFI void tma2dh(uint32_t dst, const CUtensorMap* m, uint32_t mb, int c0, int c1, uint64_t pol) {
  asm volatile("{\n.reg .pred q;\nelect.sync _|q, 0xffffffff;\n@q cp.async.bulk.tensor.2d.shared::cluster.global.mbarrier::complete_tx::bytes.L2::cache_hint [%0], [%1, {%3, %4}], [%2], %5;\n}"
    :: "r"(dst), "l"(m), "r"(mb), "r"(c0), "r"(c1), "l"(pol) : "memory");
}
DEFI void tma3d(uint32_t dst, const CUtensorMap* m, uint32_t mb, int c1, int c2) {
  asm volatile("{\n.reg .pred q;\nelect.sync _|q, 0xffffffff;\n@q cp.async.bulk.tensor.3d.shared::cluster.global.mbarrier::complete_tx::bytes [%0], [%1, {%3, %4, %5}], [%2];\n}"
    :: "r"(dst), "l"(m), "r"(mb), "r"(0), "r"(c1), "r"(c2) : "memory");
}
DEFI void tma4d(uint32_t dst, const CUtensorMap* m, uint32_t mb, int c0, int c3) {
  asm volatile("{\n.reg .pred q;\nelect.sync _|q, 0xffffffff;\n@q cp.async.bulk.tensor.4d.shared::cluster.global.mbarrier::complete_tx::bytes [%0], [%1, {%3, %4, %4, %5}], [%2];\n}"
    :: "r"(dst), "l"(m), "r"(mb), "r"(c0), "r"(0), "r"(c3) : "memory");
}
DEFI void bulk_ld(uint32_t dst, const void* src, uint32_t bytes, uint32_t mb) {
  asm volatile("{\n.reg .pred q;\nelect.sync _|q, 0xffffffff;\n@q cp.async.bulk.shared::cluster.global.mbarrier::complete_tx::bytes.L2::cache_hint [%0], [%1], %2, [%3], %4;\n}"
    :: "r"(dst), "l"(src), "r"(bytes), "r"(mb), "l"(pol_stream(HINT & 8)) : "memory");
}
DEFI void wg_fence() { asm volatile("wgmma.fence.sync.aligned;" ::: "memory"); }
DEFI void wg_commit() { asm volatile("wgmma.commit_group.sync.aligned;" ::: "memory"); }
template <int N> DEFI void wg_wait() { asm volatile("wgmma.wait_group.sync.aligned %0;" :: "n"(N) : "memory"); }
template <int N> DEFI void reg_zero(float* d) {
#pragma unroll
  for (int i = 0; i < N; i++) d[i] = 0.f;
}
template <int N> DEFI void reg_fence(float* d) {
#pragma unroll
  for (int i = 0; i < N; i++) asm volatile("" : "+f"(d[i]) :: "memory");
}
DEFI uint32_t desc_k(uint32_t a) { return ((a & 0x3FFFF) >> 4) | (1u << 16); }
DEFI uint32_t desc_mn(uint32_t a) { return ((a & 0x3FFFF) >> 4) | (512u << 16); }
DEFI void wg_rs128(float* d, const uint32_t (&a)[4], uint32_t b, uint32_t sd) {
  asm volatile("{\n.reg .pred p;\n.reg .b64 db;\nmov.b64 db, {%68, 0x40000040};\nsetp.ne.u32 p, %69, 0;\nwgmma.mma_async.sync.aligned.m64n128k16.f32.bf16.bf16 {%0,%1,%2,%3,%4,%5,%6,%7,%8,%9,%10,%11,%12,%13,%14,%15,%16,%17,%18,%19,%20,%21,%22,%23,%24,%25,%26,%27,%28,%29,%30,%31,%32,%33,%34,%35,%36,%37,%38,%39,%40,%41,%42,%43,%44,%45,%46,%47,%48,%49,%50,%51,%52,%53,%54,%55,%56,%57,%58,%59,%60,%61,%62,%63}, {%64,%65,%66,%67}, db, p, 1, 1, 1;\n}"
    : "+f"(d[0]), "+f"(d[1]), "+f"(d[2]), "+f"(d[3]), "+f"(d[4]), "+f"(d[5]), "+f"(d[6]), "+f"(d[7]), "+f"(d[8]), "+f"(d[9]), "+f"(d[10]), "+f"(d[11]), "+f"(d[12]), "+f"(d[13]), "+f"(d[14]), "+f"(d[15]), "+f"(d[16]), "+f"(d[17]), "+f"(d[18]), "+f"(d[19]), "+f"(d[20]), "+f"(d[21]), "+f"(d[22]), "+f"(d[23]), "+f"(d[24]), "+f"(d[25]), "+f"(d[26]), "+f"(d[27]), "+f"(d[28]), "+f"(d[29]), "+f"(d[30]), "+f"(d[31]), "+f"(d[32]), "+f"(d[33]), "+f"(d[34]), "+f"(d[35]), "+f"(d[36]), "+f"(d[37]), "+f"(d[38]), "+f"(d[39]), "+f"(d[40]), "+f"(d[41]), "+f"(d[42]), "+f"(d[43]), "+f"(d[44]), "+f"(d[45]), "+f"(d[46]), "+f"(d[47]), "+f"(d[48]), "+f"(d[49]), "+f"(d[50]), "+f"(d[51]), "+f"(d[52]), "+f"(d[53]), "+f"(d[54]), "+f"(d[55]), "+f"(d[56]), "+f"(d[57]), "+f"(d[58]), "+f"(d[59]), "+f"(d[60]), "+f"(d[61]), "+f"(d[62]), "+f"(d[63])
    : "r"(a[0]), "r"(a[1]), "r"(a[2]), "r"(a[3]), "r"(b), "r"(sd));
}
DEFI void wg_rs64(float* d, const uint32_t (&a)[4], uint32_t b, uint32_t sd) {
  asm volatile("{\n.reg .pred p;\n.reg .b64 db;\nmov.b64 db, {%36, 0x40000040};\nsetp.ne.u32 p, %37, 0;\nwgmma.mma_async.sync.aligned.m64n64k16.f32.bf16.bf16 {%0,%1,%2,%3,%4,%5,%6,%7,%8,%9,%10,%11,%12,%13,%14,%15,%16,%17,%18,%19,%20,%21,%22,%23,%24,%25,%26,%27,%28,%29,%30,%31}, {%32,%33,%34,%35}, db, p, 1, 1, 1;\n}"
    : "+f"(d[0]), "+f"(d[1]), "+f"(d[2]), "+f"(d[3]), "+f"(d[4]), "+f"(d[5]), "+f"(d[6]), "+f"(d[7]), "+f"(d[8]), "+f"(d[9]), "+f"(d[10]), "+f"(d[11]), "+f"(d[12]), "+f"(d[13]), "+f"(d[14]), "+f"(d[15]), "+f"(d[16]), "+f"(d[17]), "+f"(d[18]), "+f"(d[19]), "+f"(d[20]), "+f"(d[21]), "+f"(d[22]), "+f"(d[23]), "+f"(d[24]), "+f"(d[25]), "+f"(d[26]), "+f"(d[27]), "+f"(d[28]), "+f"(d[29]), "+f"(d[30]), "+f"(d[31])
    : "r"(a[0]), "r"(a[1]), "r"(a[2]), "r"(a[3]), "r"(b), "r"(sd));
}
DEFI void wg_rs64k(float* d, const uint32_t (&a)[4], uint32_t b, uint32_t sd) {
  asm volatile("{\n.reg .pred p;\n.reg .b64 db;\nmov.b64 db, {%36, 0x40000040};\nsetp.ne.u32 p, %37, 0;\nwgmma.mma_async.sync.aligned.m64n64k16.f32.bf16.bf16 {%0,%1,%2,%3,%4,%5,%6,%7,%8,%9,%10,%11,%12,%13,%14,%15,%16,%17,%18,%19,%20,%21,%22,%23,%24,%25,%26,%27,%28,%29,%30,%31}, {%32,%33,%34,%35}, db, p, 1, 1, 0;\n}"
    : "+f"(d[0]), "+f"(d[1]), "+f"(d[2]), "+f"(d[3]), "+f"(d[4]), "+f"(d[5]), "+f"(d[6]), "+f"(d[7]), "+f"(d[8]), "+f"(d[9]), "+f"(d[10]), "+f"(d[11]), "+f"(d[12]), "+f"(d[13]), "+f"(d[14]), "+f"(d[15]), "+f"(d[16]), "+f"(d[17]), "+f"(d[18]), "+f"(d[19]), "+f"(d[20]), "+f"(d[21]), "+f"(d[22]), "+f"(d[23]), "+f"(d[24]), "+f"(d[25]), "+f"(d[26]), "+f"(d[27]), "+f"(d[28]), "+f"(d[29]), "+f"(d[30]), "+f"(d[31])
    : "r"(a[0]), "r"(a[1]), "r"(a[2]), "r"(a[3]), "r"(b), "r"(sd));
}
DEFI void wg_rs16k(float* d, const uint32_t (&a)[4], uint32_t b, uint32_t sd) {
  asm volatile("{\n.reg .pred p;\n.reg .b64 db;\nmov.b64 db, {%12, 0x40000040};\nsetp.ne.u32 p, %13, 0;\nwgmma.mma_async.sync.aligned.m64n16k16.f32.bf16.bf16 {%0,%1,%2,%3,%4,%5,%6,%7}, {%8,%9,%10,%11}, db, p, 1, 1, 0;\n}"
    : "+f"(d[0]), "+f"(d[1]), "+f"(d[2]), "+f"(d[3]), "+f"(d[4]), "+f"(d[5]), "+f"(d[6]), "+f"(d[7])
    : "r"(a[0]), "r"(a[1]), "r"(a[2]), "r"(a[3]), "r"(b), "r"(sd));
}
DEFI void wg_ss256(float* d, uint32_t a, uint32_t b, uint32_t sd) {
  asm volatile("{\n.reg .pred p;\n.reg .b64 da, db;\nmov.b64 da, {%128, 0x40000040};\nmov.b64 db, {%129, 0x40000040};\nsetp.ne.u32 p, %130, 0;\nwgmma.mma_async.sync.aligned.m64n256k16.f32.bf16.bf16 {%0,%1,%2,%3,%4,%5,%6,%7,%8,%9,%10,%11,%12,%13,%14,%15,%16,%17,%18,%19,%20,%21,%22,%23,%24,%25,%26,%27,%28,%29,%30,%31,%32,%33,%34,%35,%36,%37,%38,%39,%40,%41,%42,%43,%44,%45,%46,%47,%48,%49,%50,%51,%52,%53,%54,%55,%56,%57,%58,%59,%60,%61,%62,%63,%64,%65,%66,%67,%68,%69,%70,%71,%72,%73,%74,%75,%76,%77,%78,%79,%80,%81,%82,%83,%84,%85,%86,%87,%88,%89,%90,%91,%92,%93,%94,%95,%96,%97,%98,%99,%100,%101,%102,%103,%104,%105,%106,%107,%108,%109,%110,%111,%112,%113,%114,%115,%116,%117,%118,%119,%120,%121,%122,%123,%124,%125,%126,%127}, da, db, p, 1, 1, 0, 1;\n}"
    : "+f"(d[0]), "+f"(d[1]), "+f"(d[2]), "+f"(d[3]), "+f"(d[4]), "+f"(d[5]), "+f"(d[6]), "+f"(d[7]), "+f"(d[8]), "+f"(d[9]), "+f"(d[10]), "+f"(d[11]), "+f"(d[12]), "+f"(d[13]), "+f"(d[14]), "+f"(d[15]), "+f"(d[16]), "+f"(d[17]), "+f"(d[18]), "+f"(d[19]), "+f"(d[20]), "+f"(d[21]), "+f"(d[22]), "+f"(d[23]), "+f"(d[24]), "+f"(d[25]), "+f"(d[26]), "+f"(d[27]), "+f"(d[28]), "+f"(d[29]), "+f"(d[30]), "+f"(d[31]), "+f"(d[32]), "+f"(d[33]), "+f"(d[34]), "+f"(d[35]), "+f"(d[36]), "+f"(d[37]), "+f"(d[38]), "+f"(d[39]), "+f"(d[40]), "+f"(d[41]), "+f"(d[42]), "+f"(d[43]), "+f"(d[44]), "+f"(d[45]), "+f"(d[46]), "+f"(d[47]), "+f"(d[48]), "+f"(d[49]), "+f"(d[50]), "+f"(d[51]), "+f"(d[52]), "+f"(d[53]), "+f"(d[54]), "+f"(d[55]), "+f"(d[56]), "+f"(d[57]), "+f"(d[58]), "+f"(d[59]), "+f"(d[60]), "+f"(d[61]), "+f"(d[62]), "+f"(d[63]), "+f"(d[64]), "+f"(d[65]), "+f"(d[66]), "+f"(d[67]), "+f"(d[68]), "+f"(d[69]), "+f"(d[70]), "+f"(d[71]), "+f"(d[72]), "+f"(d[73]), "+f"(d[74]), "+f"(d[75]), "+f"(d[76]), "+f"(d[77]), "+f"(d[78]), "+f"(d[79]), "+f"(d[80]), "+f"(d[81]), "+f"(d[82]), "+f"(d[83]), "+f"(d[84]), "+f"(d[85]), "+f"(d[86]), "+f"(d[87]), "+f"(d[88]), "+f"(d[89]), "+f"(d[90]), "+f"(d[91]), "+f"(d[92]), "+f"(d[93]), "+f"(d[94]), "+f"(d[95]), "+f"(d[96]), "+f"(d[97]), "+f"(d[98]), "+f"(d[99]), "+f"(d[100]), "+f"(d[101]), "+f"(d[102]), "+f"(d[103]), "+f"(d[104]), "+f"(d[105]), "+f"(d[106]), "+f"(d[107]), "+f"(d[108]), "+f"(d[109]), "+f"(d[110]), "+f"(d[111]), "+f"(d[112]), "+f"(d[113]), "+f"(d[114]), "+f"(d[115]), "+f"(d[116]), "+f"(d[117]), "+f"(d[118]), "+f"(d[119]), "+f"(d[120]), "+f"(d[121]), "+f"(d[122]), "+f"(d[123]), "+f"(d[124]), "+f"(d[125]), "+f"(d[126]), "+f"(d[127])
    : "r"(a), "r"(b), "r"(sd));
}

DEFI void poll_flags(const uint32_t* g_flags, int idx, uint32_t tgt, bool act) {
  const uint32_t* p = g_flags + (act ? idx : 0);
  for (uint32_t n = 0;; n++) {
    uint32_t v; asm volatile("ld.acquire.gpu.global.u32 %0, [%1];" : "=r"(v) : "l"(p) : "memory");
    if (uni(!act || v >= tgt)) break;
    if (n > (1u << 21)) *(volatile uint32_t*)8 = 0;
    __nanosleep(64);
  }
  asm volatile("fence.proxy.async.global;" ::: "memory");
}

struct Params {
  CUtensorMap wq, wk, wv;
  CUtensorMap wqc, wkc, wvc;
  CUtensorMap wo, wd;
  CUtensorMap wg, wu;
  CUtensorMap x, kvl, ohl;
  CUtensorMap kvc, kvm;
  CUtensorMap kp;
  CUtensorMap kvx;
  CUtensorMap st[3];
  const bf16* mem0; const bf16* gate_w;
  bf16* out;
  const char* pf[5];
  uint32_t zero; uint32_t isA; uint32_t cmap;
};

constexpr uint32_t O_BUF0 = 0, O_BUF1 = 65536, O_BUF2 = 131072, O_MEM = 196608, O_QK = O_MEM + 8192, O_SC = O_QK + 4096, O_VF = O_SC + 3072,
                   O_OS = O_VF + 4096, O_EX = O_OS + 2048, O_RS = O_EX + 2048;
constexpr uint32_t NSL = 12, O_STG = NSL * 16384, O_BAR = O_STG + 32768, O_WB = O_BAR + 256, SMEM_BYTES = O_BAR + 1536 + 1024;
static_assert(O_RS + 8 * 544 + 32 <= O_BAR && O_EX % 1024 == 0, "chain smem");
constexpr uint32_t B_SC = 16 * 8, B_V = 17 * 8, B_KV = 18 * 8, B_RS = 24 * 8, B_I0 = 26 * 8, B_ROLE = 30 * 8;
constexpr uint32_t W_FULL = 0, W_EMPTY = 96, W_STF = 192, W_STE = 208, W_DONE = 224, W_REQ = 232, W_RES = 240, W_NEXT = 248, W_INFO = 256, W_DESC = 320, W_ROLE = 448, W_DRY = 512;
constexpr int BAR_QK = 1, BAR_O = 2, BAR_S = 3, BAR_G = 4, BAR_LD = 5, BAR_A = 6, BAR_E = 7, BAR_SK = 8, BAR_R = 9;

#define NQ0 4
#define NQ1 8
#define SPLIT 1
#define TRA 1
#define TRL 1
#define EXP 0
#define GLATE 2
#define DLY2 DLY
#define NO3 12
#define VPIN 9
#define NQ2 14
#define NOV 2
#define NO1 5
#define NO2 11
#define VAT 2
#define GSP 0
#define DLY 30
#define DLA 10
#define DLB 15
#define DLV 15
#define SHIFT 1
#define CLA 5
#define PUB 1
#define NOMAX 3
#define LNORM 0
#define X4 1
#define CLL 4
#define LATE 1
#define SKQ 8
#define SKF 7
#define SKO 0
#define SKA 1
#define QMERGE 1
#define OZ 0
#define PFS 70
#define NCS 128
#define VE 0
#define RG 216
#define XVL 0
#define NQX NQ0
#define XEARLY 0
#define DRY 1
#define QPF 1
#define SK1 0
#define CLO CLA
#define ROT 1
#define SKEW 5
#define PFM 0
#define PFN 528
#define NPR 2
#define TMP 0
#define KVT 2
#define UMAP 0x0011234523456677ull
constexpr int NG = 4;
__host__ __device__ constexpr int ubar(int U) { return (int)((UMAP >> (60 - 4 * U)) & 15); }
__host__ __device__ constexpr int unit_of(int kh, int ii) { int n = 0; for (int G = 0; G < 4; G++) for (int U = 0; U < 16; U++) if (ubar(U) == 2 * G + kh && n++ == ii) return U; return -1; }
__host__ __device__ constexpr int upos(int U) { for (int ii = 0; ii < 8; ii++) if (unit_of(ubar(U) & 1, ii) == U) return (ubar(U) & 1) * 8 + ii; return -1; }
__host__ __device__ constexpr int gbeg(int kh, int G) { int n = 0; for (int U = 0; U < 16; U++) n += (ubar(U) & 1) == kh && (ubar(U) >> 1) < G; return n; }
constexpr int NGU = (ubar(unit_of(0, 7)) >> 1) + 1;
__host__ __device__ constexpr int bar_tx(int b) { return (gbeg(b & 1, (b >> 1) + 1) - gbeg(b & 1, b >> 1)) * 512 - (ubar(0) == b) * 256 - (ubar(8) == b) * 256; }
__host__ __device__ constexpr int bar_cnt(int b) { return 1 + 2 * (ubar(0) == b) + 2 * (ubar(8) == b); }
static_assert(gbeg(0, 4) == 8 && gbeg(1, 4) == 8 && gbeg(0, 1) == gbeg(1, 1) && gbeg(0, 2) == gbeg(1, 2) && gbeg(0, 3) == gbeg(1, 3), "same groups for both halves");
__host__ __device__ constexpr unsigned long long txs() { unsigned long long v = 0; for (int b = 0; b < 8; b++) v |= (unsigned long long)(bar_tx(b) / 256) << (b * 8); return v; }
constexpr unsigned long long TXS = txs();
constexpr float SCL2 = 0.08838834764831845f * 1.4426950408889634f;

DEFI void chain_kv_load(const Params& P, uint32_t sb, int h, int j, int s) {
  const int i = s & 3; const uint32_t mb = sb + O_BAR + B_KV + i * 8, d = sb + O_BUF0 + i * 12288;
  arrive_tx_e(mb, 12288);
  tma4d(d, &P.kp, mb, h * 128 + j * 64, s * 2);
  tma2d(d + 4096, &P.kvc, mb, 4096 + h * 128, s * 32);
  tma2d(d + 8192, &P.kvc, mb, 4096 + h * 128 + 64, s * 32);
}
template <int N> DEFI uint32_t delay(uint32_t x) {
  float t = __uint_as_float(x);
#pragma unroll
  for (int i = 0; i < N; i++) asm volatile("add.f32 %0, %0, %0;" : "+f"(t));
  return __float_as_uint(t);
}

template <bool XROLE>
DEFI void chain_comm(const Params& P, const uint32_t sb, const uint32_t r, const int c, const int h, const int j, const int u, const int side, uint32_t word) {
  const int lane = threadIdx.x & 31, gid = lane >> 2, tig = lane & 3, mi = lane >> 3, rr = lane & 7;
  constexpr int KH = XROLE ? 0 : 1;
  uint32_t* const g_flags = flags_base(side);
  const uint32_t zero = P.zero;
  const uint32_t bar = sb + O_BAR;
  const uint32_t bsel = (gid & 1) ? 0x3F800000u : 0x00003F80u;
  const uint32_t bs0 = opq(gid < 4 ? bsel : 0), bs1 = opq(gid < 4 ? 0 : bsel);
  const uint32_t l8 = opq(lane * 8);
  const uint32_t rsr = opq(sb + O_RS + tig * 544 + u * 128 + gid * 4);
  const uint32_t la = opq(XROLE ? u * 2048 + ((mi & 1) * 8 + rr) * 128 + (((mi >> 1) ^ rr) << 4) : sb + O_QK + (u - 2) * 1024 + (mi & 1) * 2048 + (mi >> 1) * 128 + rr * 16);
  const uint32_t lb = opq(sb + O_QK + (XROLE ? 0 : (u - 2) * 1024 + 256) + (mi >> 1) * 512 + (mi & 1) * 128 + rr * 16);
  const uint32_t vx = opq(4096 + (u >> 1) * 4096 + (rr + 8 * (mi >> 1)) * 128 + (((((4 * u) & 7) + (mi & 1)) ^ rr) << 4));
  const uint32_t scw = opq(sb + O_SC + (XROLE ? u * 512 + (lane ^ (gid & 2)) * 16 : 1024 + (u - 2) * 256 + lane * 8));
  const uint32_t scx = opq(sb + O_SC + tig * 64 + ((gid ^ ((tig & 2) << 1)) * 8));
  const uint32_t rearm = XROLE ? 0 : opq(u != 2 ? 0xFFFFFFFFu : lane < 8 ? (uint32_t)((TXS >> (lane * 8)) & 255) * 256 : lane == 16 ? 1536 : lane == 24 ? (SPLIT ? 2048 : 4096) : lane == 25 && SPLIT ? 2048 : 0xFFFFFFFFu);
  const uint32_t d1a = opq(mapa(sb + O_MEM + upos(KH * 8) * 512 + 256 + (u & 1) * 128 + lane * 4, (r + 1) & 15)), d1b = opq(mapa(bar + ubar(KH * 8) * 8, (r + 1) & 15));
  uint32_t kvf = 0;
  const uint32_t ones[4] = {0x3F803F80u, 0x3F803F80u, 0x3F803F80u, 0x3F803F80u};
  auto bcast = [&](const uint32_t zv) {
    st_async1(d1a, d1b, word);
    const uint32_t t0 = d1b | (word & zero);
    sts32(sb + O_MEM + upos(KH * 8) * 512 + (u & 1) * 128 + ((l8 | zv) >> 1), word); arrive_tx_e(bar + ubar(KH * 8) * 8, 0);
    const uint32_t dl = d1a - t0;
#pragma unroll
    for (int i = 2; i < 16; i++) {
      const int db = (ubar(KH * 8 + (i >> 1)) - ubar(KH * 8)) * 8;
      const uint32_t mb = (t0 + (((i - 1) << 24) + db)) & 0x0FFFFFFFu;
      st_async1(mb + dl + ((upos(KH * 8 + (i >> 1)) - upos(KH * 8)) * 512 + ((i & 1) - 1) * 256 - db), mb, word);
    }
  };
  auto first_kv = [&]() {
    if (!XROLE && u == 3) { bar_sync(BAR_G + 8, 288); poll_flags(g_flags, F_KV + h, KVT, true); chain_kv_load(P, sb, h, j, 0); chain_kv_load(P, sb, h, j, 1); TP(7); }
    mbar_spin(bar + B_KV, 0);
  };
  if (ROT) { bcast(0); first_kv(); }
  for (int s = 0;; s++) {
    const uint32_t ph = s & 1;
    const uint32_t zv = s & zero;
    if (!ROT) {
      bcast(zv);
      if (s == NSEG - 1) { bar_arrive(BAR_QK, 384); break; }
      if (s == 0) first_kv();
    }
    uint32_t va[2][2][4], ka[4][4];
    const uint32_t kvb = sb + O_BUF0 + (s & 3) * 12288;
    auto load_v = [&]() { const uint32_t v2 = (vx | zv) ^ 32; ldsm4t(va[0][0], kvb + vx); ldsm4t(va[1][0], kvb + v2); ldsm4t(va[0][1], kvb + vx + 2048); ldsm4t(va[1][1], kvb + v2 + 2048); };
    if (XROLE) { const uint32_t lz = la | zv; ldsm4(ka[0], kvb + la); ldsm4(ka[1], kvb + (lz ^ 32)); ldsm4(ka[2], kvb + (lz ^ 64)); ldsm4(ka[3], kvb + (lz ^ 96)); }
    if (!XROLE || !XVL) load_v();
    if (!XROLE && NEX && u == 2 && s >= PFS && s < PFS + 4)
      asm volatile("{\n.reg .pred q;\nelect.sync _|q, 0xffffffff;\n@q cp.async.bulk.prefetch.L2.global [%0], 16384;\n}" :: "l"(P.pf[4] + (((s - PFS) * 64 + c * 16 + r) << 14)) : "memory");
    if (!XROLE && u == 3 && s + 2 < NSEG - 1) {
      if (!(s & 1)) { if (kvf < KVT) poll_flags(g_flags, F_KV + ((s + 2) >> 1) * 32 + h, KVT, true); else asm volatile("fence.proxy.async.global;" ::: "memory"); }
      chain_kv_load(P, sb, h, j, s + 2);
      if (s & 1) asm volatile("ld.relaxed.gpu.global.u32 %0, [%1];" : "=r"(kvf) : "l"(g_flags + F_KV + (((s + 3) >> 1) & 31) * 32 + h) : "memory");
    }
    const uint32_t scr = (scw + 1536 + zv) ^ 0x01000000u, sbr = (bar + B_SC) ^ 0x01000000u;
    bar_sync(BAR_QK, 384);
    if (XROLE) {
      uint32_t l0[4], h0[4], l1[4], h1[4];
      ldsm4(l0, lb); ldsm4(h0, lb + 2048); ldsm4(l1, lb + 1024); ldsm4(h1, lb + 3072);
      float c0[4], c1[4];
      mmaz(c0, ka[0], hadd2(l0[0], h0[0]), hadd2(l0[1], h0[1])); mmaz(c1, ka[1], hadd2(l0[2], h0[2]), hadd2(l0[3], h0[3]));
      if (X4) {
        float c2[4], c3[4];
        mmaz(c2, ka[2], hadd2(l1[0], h1[0]), hadd2(l1[1], h1[1])); mmaz(c3, ka[3], hadd2(l1[2], h1[2]), hadd2(l1[3], h1[3]));
#pragma unroll
        for (int i = 0; i < 4; i++) { c0[i] += c1[i]; c1[i] = c2[i] + c3[i]; }
      } else { mma(c0, ka[2], hadd2(l1[0], h1[0]), hadd2(l1[1], h1[1])); mma(c1, ka[3], hadd2(l1[2], h1[2]), hadd2(l1[3], h1[3])); }
      const uint32_t x = __float_as_uint(c0[0] + c1[0]), y = __float_as_uint(c0[2] + c1[2]), z = __float_as_uint(c0[1] + c1[1]), w = __float_as_uint(c0[3] + c1[3]);
      st_async4(scr, sbr, x, y, z, w); sts128(scw, x, y, z, w);
    } else {
      uint32_t a0[4], a1[4], l0[4], h0[4];
      ldsm4(l0, lb); ldsm4(h0, lb + 2048); ldsm4(a0, la); ldsm4(a1, la + 512);
      float c0[4], c1[4];
      mmaz(c0, a0, hadd2(l0[0], h0[0]), hadd2(l0[1], h0[1])); mmaz(c1, a1, hadd2(l0[2], h0[2]), hadd2(l0[3], h0[3]));
      const uint32_t x = __float_as_uint((c0[0] + c0[2]) + (c1[0] + c1[2])), y = __float_as_uint((c0[1] + c0[3]) + (c1[1] + c1[3]));
      st_async2(scr, sbr, x, y); sts64(scw, x, y);
      arrive_tx_p(bar + l8, rearm, rearm != 0xFFFFFFFFu);
    }
    bar_sync(BAR_S, 128);
    if (XROLE && XVL) load_v();
    float x[10];
    { float z0, z1;
#pragma unroll
      for (int t = 0; t < 4; t++) lds64f(x[2 * t], x[2 * t + 1], scx + t * 256);
      lds64f(x[8], x[9], sb + O_SC + 1024 + l8); lds64f(z0, z1, sb + O_SC + 1280 + l8);
      x[8] += z0; x[9] += z1; }
    mbar_spin(bar + B_SC, ph);
    uint32_t p[5], vm0[4], vm1[4];
    {
      const uint32_t vma = sb + O_VF + u * 1024 + l8;
      float y[10], z0, z1;
      if (!NOMAX) { lds64f(y[8], y[9], sb + O_SC + 1536 + 1024 + l8); lds64f(z0, z1, sb + O_SC + 1536 + 1280 + l8); }
#pragma unroll
      for (int t = 0; t < 4; t++) lds64f(y[2 * t], y[2 * t + 1], scx + 1536 + t * 256);
      if (NOMAX) { lds64f(y[8], y[9], sb + O_SC + 1536 + 1024 + l8); lds64f(z0, z1, sb + O_SC + 1536 + 1280 + l8); }
      const bool vok = mbar_try(bar + B_V, ph);
#pragma unroll
      for (int t = 0; t < 10; t++) x[t] += y[t];
      x[8] += z0; x[9] += z1;
      const float am = fmaxf(fmaxf(fmaxf(fmaxf(fabsf(x[8]), fabsf(x[9])), fmaxf(fabsf(x[0]), fabsf(x[1]))), fmaxf(fmaxf(fabsf(x[2]), fabsf(x[3])), fmaxf(fabsf(x[4]), fabsf(x[5])))), fmaxf(fabsf(x[6]), fabsf(x[7])));
      float nb = 0.f;
#pragma unroll
      for (int t = 0; t < NOMAX; t++) p[t] = pack(ex2(x[2 * t] * SCL2), ex2(x[2 * t + 1] * SCL2));
      if (__builtin_expect(!uni(vok && am <= 40.f / SCL2), 0)) {
        mbar_spin(bar + B_V, ph);
        float mx = fmaxf(fmaxf(fmaxf(fmaxf(x[8], x[9]), fmaxf(x[0], x[1])), fmaxf(fmaxf(x[2], x[3]), fmaxf(x[4], x[5]))), fmaxf(x[6], x[7]));
        mx = fmaxf(mx, __shfl_xor_sync(0xffffffffu, mx, 1));
        mx = fmaxf(mx, __shfl_xor_sync(0xffffffffu, mx, 2));
        nb = uni(am <= 40.f / SCL2) ? 0.f : -mx * SCL2;
#pragma unroll
        for (int t = 0; t < NOMAX; t++) p[t] = pack(ex2(fmaf(x[2 * t], SCL2, nb)), ex2(fmaf(x[2 * t + 1], SCL2, nb)));
      }
      lds64(vm0[0], vm0[1], vma); lds64(vm0[2], vm0[3], vma + 256); lds64(vm1[0], vm1[1], vma + 512); lds64(vm1[2], vm1[3], vma + 768);
#pragma unroll
      for (int t = NOMAX; t < 5; t++) p[t] = pack(ex2(fmaf(x[2 * t], SCL2, nb)), ex2(fmaf(x[2 * t + 1], SCL2, nb)));
    }
    float o0[4], o1[4], sm[4];
    if (XROLE || !LNORM) mmaz(sm, ones, p[0], p[1]);
    mmaz(o0, va[0][0], p[0], p[1]); mmaz(o1, va[1][0], p[0], p[1]);
    if (XROLE || !LNORM) mma(sm, ones, p[2], p[3]);
    mma(o0, va[0][1], p[2], p[3]); mma(o1, va[1][1], p[2], p[3]);
    if (XROLE || !LNORM) mma8(sm, ones[0], ones[1], p[4]);
    mma(o0, vm0, p[4], p[4]); mma(o1, vm1, p[4], p[4]);
    {
      const float i0 = rcpa(sm[0]), i1 = rcpa(sm[1]);
      stsm4t(sb + O_OS + u * 512 + 2 * (l8 | zv), pack(o0[0] * i0, o0[1] * i1), pack(o0[2] * i0, o0[3] * i1), pack(o1[0] * i0, o1[1] * i1), pack(o1[2] * i0, o1[3] * i1));
      bar_arrive(BAR_O, 384);
    }
    char* gs = win_base() + ((s & 1) * 131072 + r * 8192 + ((r ^ (r >> 3) ^ s ^ side) & 1) * 4096 + u * 256) + l8;
    char* gw = gs + c * 1024;
    if (s + 1 < NSEG - 1) mbar_spin(bar + B_KV + ((s + 1) & 3) * 8 + ((uint32_t)((uintptr_t)gw ^ ((uintptr_t)gw >> 32)) & zero), ((s + 1) >> 2) & 1);
    const uint32_t tag = s + 1;
    float lo, hi;
    {
      mbar_spin(bar + B_RS + (SPLIT ? KH * 8 : 0), ph);
      uint32_t L0[4], L1[4];
#pragma unroll
      for (int i = 0; i < 4; i++) L0[i] = lds32(rsr + i * 32);
#pragma unroll
      for (int i = 0; i < 4; i++) L1[i] = lds32(rsr + 2176 + i * 32);
      if ((EXP == 2 || NQX > NQ0) && XROLE && XEARLY) bar_arrive(BAR_E, 320);
      float a0[4], a1[4];
      mmaz(a0, L0, bs0, bs1); mmaz(a1, L1, bs0, bs1);
      const bool od = l8 & 8;
      lo = (od ? a0[2] : a0[0]) + (od ? a1[2] : a1[0]); hi = (od ? a0[3] : a0[1]) + (od ? a1[3] : a1[1]);
      lo = __uint_as_float(__byte_perm(__float_as_uint(lo), tag, 0x3214)); hi = __uint_as_float(__byte_perm(__float_as_uint(hi), tag, 0x3214));
      asm volatile("st.volatile.global.v2.f32 [%0], {%1,%2};" :: "l"(gw), "f"(lo), "f"(hi) : "memory");
    }
    if ((EXP == 2 || NQX > NQ0) && XROLE && !XEARLY) bar_arrive(BAR_E, 320);
    if (NQ1 > NQX && KH == TRA) bar_arrive(BAR_A, 320);
    gs += delay<(XROLE ? DLY : DLY2)>(lds32(rsr)) & zero;
    bool first = true, ok;
    do {
      float y[3][2];
#pragma unroll
      for (int i = 0; i < 3; i++) asm volatile("ld.volatile.global.v2.f32 {%0,%1}, [%2];" : "=f"(y[i][0]), "=f"(y[i][1]) : "l"(gs + ((c + 1 + i) & 3) * 1024) : "memory");
      if (KH == TRL) {
        if (ROT) asm volatile("{\n.reg .pred q;\nsetp.ne.u32 q, %0, 0;\n@q bar.arrive %1, 320;\n}" :: "r"((uint32_t)first), "n"(BAR_LD) : "memory");
        else if (first) bar_arrive(BAR_LD, 320);
      }
      first = false;
      uint32_t bad = 0;
#pragma unroll
      for (int i = 0; i < 3; i++) bad |= (__float_as_uint(y[i][0]) ^ tag) | (__float_as_uint(y[i][1]) ^ tag);
      word = pack((lo + y[1][0]) + (y[0][0] + y[2][0]), (hi + y[1][1]) + (y[0][1] + y[2][1]));
      ok = uni((bad & 0xFF) == 0);
    } while (__builtin_expect(!ok, 0));
    if (ROT) {
      bcast(zv);
      if (s == NSEG - 2) { bar_arrive(BAR_QK, 384); break; }
    }
  }
}

DEFI void chain_loop(const Params& P, const uint32_t sb, const uint32_t r, const int c, const int h, const int j, const int w, const uint32_t l16, uint32_t* const g_flags,
                     uint32_t (&wq)[16][4], const uint32_t (&wk)[16][4], const uint32_t (&wv)[16][4]) {
  const uint32_t zero = P.zero, bar = sb + O_BAR;
  const int g = w & 3, kh = w >> 2;
  const uint32_t fq = sb + O_BUF2 + w * 8192 + l16, fo = fq - 65536;
  const uint32_t dst = 8 * j + ((w + (r >> 1)) & 7);
  const uint32_t mrd = sb + O_MEM + kh * 4096 + l16;
  const uint32_t rsw0 = mapa(sb + O_RS + (r >> 1) * 544, dst), rsb = mapa(bar + B_RS, dst);
  const uint32_t qst = opq(sb + O_QK + w * 512 + l16), rsw = opq(rsw0 + (l16 >> 1));
  const uint32_t vfr = opq((sb + O_VF + (4 * j + g) * 512 + kh * 256 + (l16 >> 1)) ^ 0x01000000u);
  for (int s = 0;; s++) {
    const uint32_t ph = s & 1, zv = s & zero;
    float q0[4], k0[4], q1[4], k1[4], v0[4], v1[4];
    uint32_t b[8][4], wo[16][4];
    mbar_spin(bar + kh * 8, ph);
#pragma unroll
    for (int G = 0; G < NGU; G++) {
#pragma unroll
      for (int ii = gbeg(0, G); ii < gbeg(0, G + 1); ii++) ldsm4(b[ii], mrd + ii * 512);
      bool pn = true;
      if (G + 1 < NGU) pn = mbar_try(bar + kh * 8 + (G + 1) * 16, ph);
      if (G == GLATE) {
#pragma unroll
        for (int f = NQ2; f < 16; f++) lds128(wq[f], fq + f * 512);
      }
#pragma unroll
      for (int ii = gbeg(0, G) - (G > 0 ? SHIFT : 0); ii < gbeg(0, G + 1) - (G < NGU - 1 ? SHIFT : 0); ii++) {
        if (ii == 0) { mmaz(q0, wq[0], b[0][0], b[0][1]); mmaz(q1, wq[1], b[0][2], b[0][3]); mmaz(k0, wk[0], b[0][0], b[0][1]); mmaz(k1, wk[1], b[0][2], b[0][3]); }
        else {
          mma(q0, wq[2 * ii], b[ii][0], b[ii][1]); mma(q1, wq[2 * ii + 1], b[ii][2], b[ii][3]);
          mma(k0, wk[2 * ii], b[ii][0], b[ii][1]); mma(k1, wk[2 * ii + 1], b[ii][2], b[ii][3]);
        }
        if (ii < VE) {
          if (ii == 0) { mmaz(v0, wv[0], b[0][0], b[0][1]); mmaz(v1, wv[1], b[0][2], b[0][3]); }
          else { mma(v0, wv[2 * ii], b[ii][0], b[ii][1]); mma(v1, wv[2 * ii + 1], b[ii][2], b[ii][3]); }
        }
      }
      if (G + 1 < NGU) mbar_fin(pn, bar + kh * 8 + (G + 1) * 16, ph);
    }
    stsm4t(qst, pack(q0[0] + q1[0], q0[1] + q1[1]), pack(q0[2] + q1[2], q0[3] + q1[3]), pack(k0[0] + k1[0], k0[1] + k1[1]), pack(k0[2] + k1[2], k0[3] + k1[3]));
    bar_arrive(BAR_QK, 384);
    sfence(zero + 1000, s);
    if (VE == 0) { mmaz(v0, wv[0], b[0][0], b[0][1]); mmaz(v1, wv[1], b[0][2], b[0][3]); }
#pragma unroll
    for (int ii = VE ? VE : 1; ii < 8; ii++) {
      if (ii == (VAT + VE > 7 ? 7 : VAT + VE)) {
        const uint32_t fo1 = fo + (__float_as_uint(v0[0]) & zero);
#pragma unroll
        for (int f = 0; f < NOV; f++) lds128(wo[f], fo1 + f * 512);
      }
      if (ii == VPIN && NOV > 0 && VPIN > VAT + VE) b[ii][0] |= wo[NOV - 1][0] & zero;
      mma(v0, wv[2 * ii], b[ii][0], b[ii][1]); mma(v1, wv[2 * ii + 1], b[ii][2], b[ii][3]);
    }
    {
      const uint32_t x = pack(v0[0] + v1[0], v0[1] + v1[1]), y = pack(v0[2] + v1[2], v0[3] + v1[3]);
      st_async2(vfr, (bar + B_V) ^ 0x01000000u, x, y);
      sts64((vfr | zv) ^ 0x01000000u, x, y);
      arrive_tx_e(bar + B_V, w == 0 ? 2048 : 0);
    }
    auto publish = [&](int n) {
      asm volatile("{\n.reg .pred q;\nelect.sync _|q, 0xffffffff;\n@q cp.async.bulk.wait_group 0;\n@q st.relaxed.gpu.global.u32 [%0], %1;\n}" :: "l"(g_flags + F_C + c * 16 + r + zv), "r"(n) : "memory");
    };
    auto ex_stage = [&]() {
      uint32_t a0, a1, b0, b1;
      const uint32_t src = sb + (kh ? O_VF + (4 * j + g) * 512 : O_QK + g * 512 + 256) + ((l16 | zv) >> 1);
      lds64(a0, a1, src); lds64(b0, b1, src + (kh ? 256 : 2048));
      a0 = hadd2(a0, b0); a1 = hadd2(a1, b1);
      const uint32_t ln = (l16 | zv) >> (kh ? 4 : 5), row = ln & 7, dsta = sb + O_EX + kh * 1024 + row * 128 + (((2 * g + ((ln >> 3) & 1)) ^ row) << 4);
      if (kh) asm volatile("stmatrix.sync.aligned.m8n8.x2.trans.shared.b16 [%0], {%1,%2};" :: "r"(dsta), "r"(a0), "r"(a1) : "memory");
      else sts64(dsta + ((l16 >> 1) & 8), a0, a1);
      fence_async_smem();
    };
    auto ex_store = [&]() {
      asm volatile("{\n.reg .pred q;\nelect.sync _|q, 0xffffffff;\n"
                   "@q cp.async.bulk.tensor.2d.global.shared::cta.bulk_group [%0, {%2, %4}], [%1];\n"
                   "@q cp.async.bulk.tensor.2d.global.shared::cta.bulk_group [%0, {%3, %4}], [%1 + 1024];\n"
                   "@q cp.async.bulk.commit_group;\n}"
                   :: "l"(&P.kvx), "r"(sb + O_EX), "r"(h * 128 + j * 64), "r"(4096 + h * 128 + j * 64), "r"(s * 8) : "memory");
    };
#pragma unroll
    for (int f = NOV; f < NO1; f++) lds128(wo[f], fo + f * 512);
    if (s == NSEG - 1) {
      if (w == 0) publish(s);
      bar_sync(BAR_G, 256); ex_stage();
      bar_sync(BAR_O, 384);
      if (w == 0) { ex_store(); publish(NSEG); }
      mbar_spin(bar + B_V, ph);
      break;
    }
    {
      mbar_spin(bar + B_SC, ph);
      const uint32_t fo2 = fo + (delay<DLB>(clk()) & zero);
#pragma unroll
      for (int f = NO1; f < NO2; f++) lds128(wo[f], fo2 + f * 512);
    }
    if (PUB == 1 && w == 0) publish(s);
    bar_sync(BAR_O, 384);
    { uint32_t ob[4][4];
#pragma unroll
      for (int i = 0; i < 4; i++) ldsm4(ob[i], sb + O_OS + i * 512 + l16);
      float i0 = 1.f, i1 = 1.f;
      if (LNORM) { lds64f(i0, i1, sb + O_RS + 8 * 544 + ((rsw | zv) & 24)); i0 = rcpa(i0); i1 = rcpa(i1); }
      mmaz(q0, wo[0], ob[0][0], ob[0][1]); mmaz(q1, wo[1], ob[0][2], ob[0][3]);
#pragma unroll
      for (int f = NO2; f < NO3; f++) lds128(wo[f], fo + f * 512);
#pragma unroll
      for (int i = 1; i < 4; i++) { mma(q0, wo[2 * i], ob[i][0], ob[i][1]); mma(q1, wo[2 * i + 1], ob[i][2], ob[i][3]);
        if (i == 2) { ob[0][0] |= __float_as_uint(q0[0]) & zero; ob[0][2] |= __float_as_uint(q1[0]) & zero; } }
      mmaz(k0, wo[8], ob[0][0], ob[0][1]); mmaz(k1, wo[9], ob[0][2], ob[0][3]);
      st_async2(rsw, rsb, pack((q0[0] + q1[0]) * i0, (q0[2] + q1[2]) * i0), pack((q0[1] + q1[1]) * i1, (q0[3] + q1[3]) * i1));
#pragma unroll
      for (int f = NO3; f < 16; f++) lds128(wo[f], fo + f * 512);
      if (GSP) { mma(k0, wo[10], ob[1][0], ob[1][1]); mma(k1, wo[11], ob[1][2], ob[1][3]); }
      sfence(zero + 5000, s);
#pragma unroll
      for (int i = 1 + GSP; i < 4; i++) { mma(k0, wo[8 + 2 * i], ob[i][0], ob[i][1]); mma(k1, wo[8 + 2 * i + 1], ob[i][2], ob[i][3]); }
      st_async2(rsw + 256, rsb + (SPLIT ? 8 : 0), pack((k0[0] + k1[0]) * i0, (k0[2] + k1[2]) * i0), pack((k0[1] + k1[1]) * i1, (k0[3] + k1[3]) * i1));
    }
#pragma unroll
    for (int f = 0; f < NQ0; f++) lds128(wq[f], fq + f * 512);
    if (PUB == 0) { if (w == 0) publish(s); bar_sync(BAR_G, 256); }
    if (EXP == 0) ex_stage();
    if (EXP == 2 || NQX > NQ0) {
      bar_sync(BAR_E, 320);
#pragma unroll
      for (int f = NQ0; f < NQX; f++) lds128(wq[f], fq + f * 512);
      if (EXP == 2) ex_stage();
    }
    if (NQ1 > NQX) {
      bar_sync(BAR_A, 320);
#pragma unroll
      for (int f = NQX; f < NQ1; f++) lds128(wq[f], fq + f * 512);
    }
    if (EXP == 1) ex_stage();
    bar_sync(BAR_LD, 320);
#pragma unroll
    for (int f = NQ1; f < NQ2; f++) lds128(wq[f], fq + f * 512);
    if (w == 0) ex_store();
    { float d[4]; mmaz(d, wq[NQ2 - 1], wk[0][0], wk[0][1]); wq[0][0] |= __float_as_uint(d[0]) & zero; }
  }
}

DEFI void chain_gemm(const Params& P, const uint32_t sb, const uint32_t r, const int c, const int h, const int j, const int w, const int side) {
  const uint32_t bar = sb + O_BAR;
  const int g = w & 3, kh = w >> 2;
  uint32_t wk[16][4], wv[16][4], wq[16][4];
  const uint32_t l16 = opq((threadIdx.x & 31) * 16);
  const uint32_t fq = sb + O_BUF2 + w * 8192 + l16, fo = fq - 65536;
  const uint32_t dst = 8 * j + ((w + (r >> 1)) & 7);
  {
    const int ln = l16 >> 4, mi = ln >> 3, rr = ln & 7;
    const uint32_t lo = sb + (8 * (mi >> 1) + rr) * 128 + (((2 * g + (mi & 1)) ^ rr) << 4);
    auto extract = [&](uint32_t (&d)[16][4], uint32_t buf) {
#pragma unroll
      for (int f = 0; f < 16; f++) { const int U = kh ? unit_of(1, f >> 1) : unit_of(0, f >> 1); ldsm4t(d[f], lo + buf + ((r - 2 * (U & 7) - (f & 1)) & 15) * 4096 + (U >> 3) * 2048); }
    };
    mbar_spin(bar + B_I0, 0);
    if (w == 0) TP(3);
    extract(wk, O_BUF2);
    fence_async_smem();
    bar_sync(BAR_G, 256);
    if (w == 0) {
      arrive_tx_e(bar + B_I0 + 24, 65536);
      tma4d(sb + O_BUF2, &P.wqc, bar + B_I0 + 24, h * 128 + j * 64, 0); tma4d(sb + O_BUF2 + 32768, &P.wqc, bar + B_I0 + 24, h * 128 + j * 64, 16);
    }
    mbar_spin(bar + B_I0 + 8, 0);
    extract(wv, O_BUF0);
    fence_async_smem();
    bar_arrive(BAR_G + 8, 288);
    mbar_spin(bar + B_I0 + 16, 0);
    if (w == 0) TP(4);
#pragma unroll
    for (int f = 0; f < 16; f++) {
      const int ch = 4 * (dst & 7) + 2 * (f >> 3) + (mi & 1);
      ldsm4t(wq[f], sb + O_BUF1 + (ch >> 4) * 32768 + ((f >> 2) & 1) * 16384 + ((ch >> 3) & 1) * 8192 + (16 * (f & 3) + 8 * (mi >> 1) + rr) * 128 + (((ch & 7) ^ rr) << 4));
    }
    fence_async_smem();
    bar_sync(BAR_G, 256);
#pragma unroll
    for (int f = 0; f < 16; f++) sts128(fo + f * 512, wq[f][0], wq[f][1], wq[f][2], wq[f][3]);
    mbar_spin(bar + B_I0 + 24, 0);
    if (w == 0) TP(5);
    extract(wq, O_BUF2);
    fence_async_smem();
    bar_sync(BAR_G, 256);
#pragma unroll
    for (int f = 15; f >= 0; f--) sts128(fq + f * 512, wq[f][0], wq[f][1], wq[f][2], wq[f][3]);
    if (w == 0) TP(9);
  }
  chain_loop(P, sb, r, c, h, j, w, l16, flags_base(side), wq, wk, wv);
}

struct Ring { uint32_t sl, ph, fl; DEFI void next() { if (++sl == NSL) { sl = 0; ph ^= fl; } }
  DEFI void skip(uint32_t n) { sl += n; if (sl >= NSL) { sl -= NSL; ph ^= fl; } } };

DEFI void claimer(const Params& P, const uint32_t sb, uint32_t* const g_flags, const bool chain, const bool near_chain) {
  const uint32_t wb = sb + O_WB; const int lane = threadIdx.x & 31;
  auto wait_b = [&](uint32_t a, uint32_t ph) { const uint32_t t0 = gtime(); while (!uni(mbar_try(a, ph))) if (gtime() - t0 > 2000000000u) *(volatile uint32_t*)8 = 0; };
  uint32_t mode = 0, ge0 = 0, ge1 = 0, gx0 = 0, gx1 = 0;
  if (chain) { ge0 = g_grp[lane]; ge1 = g_grp[lane + 32]; gx0 = g_grp[lane + 64]; gx1 = g_grp[lane + 96]; mode = 1; }
  if (NCS && near_chain && !chain) {
    const uint32_t t0 = gtime(); uint32_t v;
    do asm volatile("ld.relaxed.gpu.global.u32 %0, [%1];" : "=r"(v) : "l"(g_flags + F_Q) : "memory"); while (uni(v < NCS && gtime() - t0 < 6000));
  }
  if (chain && NEX) wait_b(wb + W_REQ, 0);
  uint32_t prev = chain && NEX ? __shfl_sync(0xffffffffu, lds32(wb + W_NEXT + 4) & 0xFFFF, 0) : 0;
  for (uint32_t ph = chain && NEX;; ph ^= 1) {
    uint32_t id = NTASK;
    if (prev - NFB < NFOL) id = prev + NFOL; else
    for (uint32_t spin = 0;; spin++) {
      if (mode) {
        uint32_t c0, c1, p0, p1, nq;
        asm volatile("ld.relaxed.gpu.global.u32 %0, [%1];" : "=r"(nq) : "l"(g_flags + F_Q) : "memory");
        asm volatile("ld.relaxed.gpu.global.u32 %0, [%1];" : "=r"(c0) : "l"(g_flags + F_G + lane) : "memory");
        asm volatile("ld.relaxed.gpu.global.u32 %0, [%1];" : "=r"(c1) : "l"(g_flags + F_G + 32 + lane) : "memory");
        asm volatile("ld.relaxed.gpu.global.u32 %0, [%1];" : "=r"(p0) : "l"(g_flags + F_H + (ge0 >> 24)) : "memory");
        asm volatile("ld.relaxed.gpu.global.u32 %0, [%1];" : "=r"(p1) : "l"(g_flags + F_H + (ge1 >> 24)) : "memory");
        const bool o0 = ge0 && c0 <= ((ge0 >> 10) & 63), o1 = ge1 && c1 <= ((ge1 >> 10) & 63);
        uint64_t om = __ballot_sync(0xffffffffu, o0) | ((uint64_t)__ballot_sync(0xffffffffu, o1) << 32);
        if (om & OPF_GROUPS) om |= 1ull << 62;
        uint32_t r0 = __ballot_sync(0xffffffffu, o0 && p0 >= ((ge0 >> 16) & 255) && nq >= (gx0 & 0xFFFF) && !((om >> (gx0 >> 16)) & 1));
        uint32_t r1 = __ballot_sync(0xffffffffu, o1 && p1 >= ((ge1 >> 16) & 255) && nq >= (gx1 & 0xFFFF) && !((om >> (gx1 >> 16)) & 1));
        const bool any = r0 | r1;
        while (r0 | r1) {
          const int f = __ffs(r0 ? r0 : r1) - 1;
          const uint32_t g1 = __shfl_sync(0xffffffffu, r0 ? ge0 : ge1, f);
          uint32_t k = 0;
          if (lane == 0) k = atomicAdd(g_flags + F_G + (r0 ? 0 : 32) + f, 1);
          k = __shfl_sync(0xffffffffu, k, 0);
          if (k <= ((g1 >> 10) & 63)) { id = (g1 & 1023) + k; break; }
          if (r0) r0 &= r0 - 1; else r1 &= r1 - 1;
        }
        if (id != NTASK) break;
        if (any && mode == 2) continue;
        if (mode == 2) {
          if (!om) break;
          if (spin > (1u << 21)) *(volatile uint32_t*)8 = 0;
          __nanosleep(50);
          continue;
        }
      }
      if (lane == 0) id = atomicAdd(g_flags + F_Q, 1);
      id = __shfl_sync(0xffffffffu, id, 0);
      if (!mode && id >= 128) { ge0 = g_grp[lane]; ge1 = g_grp[lane + 32]; gx0 = g_grp[lane + 64]; gx1 = g_grp[lane + 96]; mode = 1; }
      if (id < NIND) break;
      id = NTASK; mode = 2;
    }
    const uint32_t t = id < 128 ? ((id >> 6) << 3) | ((id & 63) << 7) | (1u << 14) : id < NTASK ? g_tasks[id] : T_EXIT;
    prev = id;
    sts64(wb + W_NEXT, t, id | (LATE && mode == 2 ? 0x80000000u : 0));
    arrive_e(wb + W_RES);
    wait_b(wb + W_REQ, ph);
    if (t == T_EXIT) break;
  }
  TP(10);
  uint32_t last = 0;
  if (lane == 0) last = atomicAdd(g_flags + F_EXIT, 1) == 131;
  if (__shfl_sync(0xffffffffu, last, 0)) { for (int i = lane; i < F_N / 4; i += 32) ((uint4*)g_flags)[i] = make_uint4(0, 0, 0, 0); g_tk = 0; }
  wait_b(wb + W_DONE, 0);
  TP(11);
}

DEFI void producer(const Params& P, const uint32_t sb, uint32_t* const g_flags) {
  const uint32_t wb = sb + O_WB; const int lane = threadIdx.x & 31;
  Ring R{0, 1, 1};
  uint32_t full, dst, left = 0;
  auto acquire = [&](uint32_t bytes, uint32_t info) {
    if (--left == 0) arrive_e(wb + W_REQ);
    mbar_spin(wb + W_EMPTY + R.sl * 8, R.ph);
    full = wb + W_FULL + R.sl * 8; dst = sb + R.sl * 16384;
    sts32(wb + W_INFO + R.sl * 4, info);
    arrive_tx_e(full, bytes);
    R.next();
  };
  auto request_late = [&](uint32_t k) {
    const bool wrap = R.sl < k;
    mbar_spin(wb + W_EMPTY + (R.sl + (wrap ? NSL : 0) - k) * 8, R.ph ^ !wrap);
    arrive_e(wb + W_REQ);
  };
  for (uint32_t ph = 0;; ph ^= 1) {
    mbar_spin(wb + W_RES, ph);
    uint32_t t, id; lds64(t, id, wb + W_NEXT);
    const bool late = __shfl_sync(0xffffffffu, id, 0) >> 31; id &= 0xFFFF;
    t = __shfl_sync(0xffffffffu, t, 0);
    if (t == T_EXIT) { left = 1; acquire(0, T_EXIT); break; }
    const int type = t & 7, m = (t >> 3) & 15, a = (t >> 7) & 127, b = (t >> 14) & 127, nh = (t >> 21) & 1, p = (t >> 22) & 63, hr = (t >> 28) & 1;
    if (type > T_QA) {
      if (type == T_RD) {
        const bool ao = t >> 29;
        poll_flags(g_flags, lane ? F_P2 + (2 * m + hr) * 2 + nh : F_P + m * 2 + nh, lane ? 2 * p : ao ? 2 : 2 * (p + 1), lane <= ao);
        left = 1; acquire(0, t); continue;
      }
      if (type == T_AO) {
        left = 0;
        poll_flags(g_flags, (lane & 1 ? F_O + m * 32 : F_KV + (2 * m + hr) * 32) + a + (lane >> 1), 2, (lane >> 1) < b);
#pragma unroll 1
        for (int n = a; n < a + b; n++) {
#pragma unroll 1
          for (int i = 0; i < 3; i++) { acquire(16384, t); const CUtensorMap* mp = &P.st[i == 0]; const int c0 = (i >> 1) * 4096 + n * 128;
            tma2d(dst, mp, full, c0, m * 128 + hr * 64); tma2d(dst + 8192, mp, full, c0 + 64, m * 128 + hr * 64); }
#pragma unroll 1
          for (int i = 0; i < 4; i++) { acquire(16384, t); tma3d(dst, &P.wo, full, n * 128 + (i >> 1) * 64, nh * 4 + (i & 1) * 2); }
          if (n == a) poll_flags(g_flags, F_C + 2 * a + lane, 4 * m + 2 * hr + 2, lane < 2 * b);
          acquire(8192, t);
          for (int i = 0; i < 4; i++) tma2d(dst + i * 2048, &P.kvm, full, (i >> 1) * 4096 + n * 128 + (i & 1) * 64, m * 32 + hr * 16);
        }
        request_late(1);
        continue;
      }
      while (R.sl % 3) acquire(0, t);
      left = b <= 4 || late ? 0 : type == T_OF ? 3 * b + 1 : max(3 * b - CLO, 1);
      const uint32_t s0 = R.sl;
      const bool late_a = b <= 4;
      auto wait_a = [&]() { if (a >= 64) poll_flags(g_flags, F_H + m, 46, true); else poll_flags(g_flags, F_O + m * 32 + (a >> 1) + lane, 2, lane < (b >> 1)); };
      if (!late_a) wait_a();
#pragma unroll 1
      for (int kb = a; kb < a + b; kb++) {
        acquire(16384, t); if (!late_a) tma2dh(dst, &P.ohl, full, kb * 64, m * 128, pol_stream(HINT & 8));
        const CUtensorMap* wm = kb < 64 ? &P.wo : &P.wd;
        acquire(16384, t); tma3d(dst, wm, full, (kb & 63) * 64, nh * 4);
        acquire(16384, t); tma3d(dst, wm, full, (kb & 63) * 64, nh * 4 + 2);
      }
      if (late_a) {
        wait_a();
#pragma unroll 1
        for (int i = 0; i < b; i++) { const uint32_t sl = (s0 + 3 * i) % NSL; tma2d(sb + sl * 16384, &P.ohl, wb + W_FULL + sl * 8, (a + i) * 64, m * 128); }
      }
      if (type == T_OF) {
        poll_flags(g_flags, F_P + m * 2 + nh, 2 * (p + 1), true);
#pragma unroll 1
        for (int i = p; i >= 0; i--)
#pragma unroll 1
          for (int q = 0; q < 4; q++) { acquire(16384, t); bulk_ld(dst, g_part + ((m * 2 + nh) * MAXP + i) * 4096 + q * 1024, 16384, full); }
      }
      acquire(0, t); acquire(0, t);
      if (late || late_a) request_late(CLL + 2);
    } else {
      left = late ? 0 : type != T_QA ? 8 + 8 * b - CLA : b > 1 ? 8 + 14 * b - CLA : 0;
#pragma unroll 1
      for (int kb = 0; kb < 8; kb++) { acquire(16384, t); tma3d(dst, &P.x, full, m * 128 + (kb >> 2) * 64, (kb & 3) * 2); }
#pragma unroll 1
      for (int n = a; n < a + b; n++) {
        if (type == T_F) {
#pragma unroll 1
          for (int kb = 0; kb < 8; kb++) { acquire(16384, t); tma2d(dst, &P.wg, full, n * 64, kb * 64); tma2d(dst + 8192, &P.wu, full, n * 64, kb * 64); }
        } else {
          const bool isq = type == T_QA || n >= 64;
          const CUtensorMap* wm = isq ? &P.wq : (n & 1) ? &P.wv : &P.wk;
          const int hh = isq ? n & 63 : n >> 1;
#pragma unroll 1
          for (int kb = 0; kb < 8; kb++) { acquire(16384, t); tma3d(dst, wm, full, kb * 64, hh * 2); }
          if (type == T_QA) {
            if (n == a) poll_flags(g_flags, F_KV + (2 * m + (lane & 1)) * 32 + a + (lane >> 1), 2, (lane >> 1) < b);
            const uint32_t s0 = R.sl;
            auto load_m = [&](int x) { const uint32_t sl = (s0 + 1 + 3 * x) % NSL;
              for (int i = 0; i < 4; i++) tma2dh(sb + sl * 16384 + i * 2048, &P.kvm, wb + W_FULL + sl * 8, (i >> 1) * 4096 + n * 128 + (i & 1) * 64, m * 32 + x * 16, pol_stream(HINT & 4)); };
#pragma unroll 1
            for (int i = 0; i < 4; i++) {
              if (i & 1) { acquire(8192, t); if (n != a) load_m(i >> 1); }
              acquire(16384, t);
              tma2dh(dst, &P.st[0], full, (i & 1) * 4096 + n * 128, m * 128 + (i >> 1) * 64, pol_stream(HINT & 4)); tma2dh(dst + 8192, &P.st[0], full, (i & 1) * 4096 + n * 128 + 64, m * 128 + (i >> 1) * 64, pol_stream(HINT & 4));
              if (n == a && (i & 1)) { poll_flags(g_flags, F_C + 2 * a + lane, 4 * m + i + 1, lane < 2 * b); load_m(i >> 1); }
            }
            if (b == 1 && !late) arrive_e(wb + W_REQ);
          }
        }
      }
      if (late) request_late(type == T_QA ? 3 : CLL);
    }
  }
}

DEFI void storer(const Params& P, const uint32_t sb, uint32_t* const g_flags, const int wg) {
  const uint32_t wb = sb + O_WB, src0 = sb + O_STG + wg * 16384;
  const int lane = threadIdx.x & 31;
  for (uint32_t ph = 0;; ph ^= 1) {
    mbar_spin(wb + W_STF + wg * 8, ph);
    uint32_t d[4]; lds128(d, wb + W_DESC + wg * 16);
    const uint32_t kind = __shfl_sync(0xffffffffu, d[0] & 255, 0);
    if (kind == T_EXIT) break;
    if (lane == 0) {
      const uint32_t nb = (d[0] >> 8) & 255;
      for (uint32_t i = 0; i < nb; i++) {
        const uint32_t src = i < 2 ? src0 : sb + (d[0] >> 16) * 16384 - 16384;
        if (kind < 3) asm volatile("cp.async.bulk.tensor.2d.global.shared::cta.bulk_group.L2::cache_hint [%0, {%2, %3}], [%1], %4;" :: "l"(&P.st[kind]), "r"(src + i * 8192), "r"(d[1] + i * 64), "r"(d[2]),
                                   "l"(pol_stream(kind == 0 ? HINT & 1 : kind == 1 ? HINT & 2 : HINT & 16)) : "memory");
        else if (kind == 4) asm volatile("cp.async.bulk.global.shared::cta.bulk_group [%0], [%1], 256;" :: "l"(g_gate + d[1]), "r"(src) : "memory");
        else asm volatile("cp.async.bulk.global.shared::cta.bulk_group.L2::cache_hint [%0], [%1], 8192, %2;" :: "l"(g_part + d[1] + i * 1024), "r"(src + i * 8192), "l"(pol_stream(HINT & 2)) : "memory");
      }
      asm volatile("cp.async.bulk.commit_group;" ::: "memory");
      asm volatile("cp.async.bulk.wait_group.read 0;" ::: "memory");
      asm volatile("mbarrier.arrive.shared::cta.b64 _, [%0];" :: "r"(wb + W_STE + wg * 8) : "memory");
      if (nb == 4) asm volatile("mbarrier.arrive.shared::cta.b64 _, [%0], 4;" :: "r"(wb + W_EMPTY + (d[0] >> 16) * 8) : "memory");
      if (d[3] != 0xFFFFFFFFu) {
        asm volatile("cp.async.bulk.wait_group 0;" ::: "memory");
        asm volatile("red.relaxed.gpu.global.add.u32 [%0], 1;" :: "l"(g_flags + d[3]) : "memory");
        if (d[3] - F_O < 512) asm volatile("red.relaxed.gpu.global.add.u32 [%0], 1;" :: "l"(g_flags + F_OT + ((d[3] - F_O) >> 5)) : "memory");
      }
    }
    __syncwarp();
  }
  if (lane == 0) asm volatile("cp.async.bulk.wait_group 0;" ::: "memory");
  __syncwarp();
}

DEFI void softmax_p(float (&v)[20], const bool sg, uint32_t (&pa)[5][4]) {
  float m0 = fmaxf(v[16], v[17]), m1 = fmaxf(v[18], v[19]);
#pragma unroll
  for (int jx = 0; jx < 4; jx++) { m0 = fmaxf(m0, fmaxf(v[4 * jx], v[4 * jx + 1])); m1 = fmaxf(m1, fmaxf(v[4 * jx + 2], v[4 * jx + 3])); }
  m0 = fmaxf(m0, __shfl_xor_sync(0xffffffffu, m0, 1)); m1 = fmaxf(m1, __shfl_xor_sync(0xffffffffu, m1, 1));
  m0 = fmaxf(m0, __shfl_xor_sync(0xffffffffu, m0, 2)); m1 = fmaxf(m1, __shfl_xor_sync(0xffffffffu, m1, 2));
  m0 *= -SCL2; m1 *= -SCL2;
  float r0 = 0.f, r1 = 0.f;
#pragma unroll
  for (int i = 0; i < 20; i++) { v[i] = ex2(fmaf(v[i], SCL2, (i & 2) ? m1 : m0)); if (i & 2) r1 += v[i]; else r0 += v[i]; }
  r0 += __shfl_xor_sync(0xffffffffu, r0, 1); r1 += __shfl_xor_sync(0xffffffffu, r1, 1);
  r0 += __shfl_xor_sync(0xffffffffu, r0, 2); r1 += __shfl_xor_sync(0xffffffffu, r1, 2);
  r0 = rcpa(r0); r1 = rcpa(r1);
#pragma unroll
  for (int k = 0; k < 2; k++)
#pragma unroll
    for (int i = 0; i < 4; i++) {
      const float rs = (i & 1) ? r1 : r0;
      const uint32_t z = pack(v[8 * k + 2 * i] * rs, v[8 * k + 2 * i + 1] * rs);
      pa[k][i] = sg ? 0u : z; pa[2 + k][i] = sg ? z : 0u;
    }
  const uint32_t z0 = pack(v[16] * r0, v[17] * r0), z1 = pack(v[18] * r1, v[19] * r1);
  pa[4][0] = sg ? 0u : z0; pa[4][1] = sg ? 0u : z1; pa[4][2] = sg ? z0 : 0u; pa[4][3] = sg ? z1 : 0u;
}
constexpr float MASKED = -1e9f / 0.08838834764831845f;

DEFI void consumer(const Params& P, const uint32_t sb, const int w, const uint32_t tid, const bool dry) {
  const int lane = tid & 31, gid = lane >> 2, tig = lane & 3, mi = lane >> 3, rr = lane & 7, wg = w >> 2, w4 = w & 3;
  const uint32_t wb = sb + O_WB + (dry ? W_DRY : 0);
  const uint32_t stg = sb + O_STG + (wg | dry) * 16384, zero = P.zero;
  const uint32_t frag = (16 * w4 + (mi & 1) * 8 + rr) * 128 + (((mi >> 1) ^ rr) << 4);
  Ring R{dry && !wg, dry, !dry};
  uint32_t sph = 1;
  auto wait_full = [&]() { mbar_spin(wb + W_FULL + R.sl * 8, R.ph); };
  auto stage_begin = [&]() { mbar_spin(wb + W_STE + wg * 8, sph); sph ^= 1; };
  auto stage_end = [&](uint32_t kind, uint32_t c0, uint32_t c1, uint32_t flag) {
    fence_async_smem();
    if (w4 == 0) sts128(wb + W_DESC + wg * 16, kind, c0, c1, flag);
    __syncwarp();
    arrive_e(wb + W_STF + wg * 8);
  };
  while (true) {
    wait_full();
    const uint32_t t = __shfl_sync(0xffffffffu, lds32(wb + W_INFO + R.sl * 4), 0);
    const int type = t & 7, m = (t >> 3) & 15, a = (t >> 7) & 127, b = (t >> 14) & 127, nh = (t >> 21) & 1, p = (t >> 22) & 63, hr = (t >> 28) & 1;
    if (__builtin_expect(type == T_EXIT, 0)) break;
    const int row0 = m * 128 + wg * 64;
    if (type > T_QA) {
      if (type == T_RD) {
        arrive_e(wb + W_EMPTY + R.sl * 8); R.next();
        if (!(t >> 29)) {
          const float g0 = __ldcg(g_gate + row0 + 16 * w4 + gid), g1 = __ldcg(g_gate + row0 + 16 * w4 + gid + 8);
#pragma unroll 1
          for (int pc = a; pc < a + b; pc++) {
            const uint4* src = g_part + (m * 2 + nh) * MAXP * 4096 + (pc >> 2) * 1024 + wg * 512 + (pc & 3) * 128 + (tid & 127);
            uint4 z[17];
#pragma unroll
            for (int i = 0; i < 17; i++) z[i] = i <= p ? __ldcg(src + i * 4096) : make_uint4(0, 0, 0, 0);
            float y[8]; reg_zero<8>(y);
#pragma unroll
            for (int i = 1; i < 17; i++) { y[0] += blo(z[i].x); y[1] += bhi(z[i].x); y[2] += blo(z[i].y); y[3] += bhi(z[i].y); y[4] += blo(z[i].z); y[5] += bhi(z[i].z); y[6] += blo(z[i].w); y[7] += bhi(z[i].w); }
            uint32_t* o = (uint32_t*)(P.out + (row0 + 16 * w4 + gid) * DM + nh * 256 + pc * 16) + tig;
            o[0] = pack(fmaf(y[0], g0, blo(z[0].x)), fmaf(y[1], g0, bhi(z[0].x))); o[4] = pack(fmaf(y[4], g0, blo(z[0].z)), fmaf(y[5], g0, bhi(z[0].z)));
            o[2048] = pack(fmaf(y[2], g1, blo(z[0].y)), fmaf(y[3], g1, bhi(z[0].y))); o[2052] = pack(fmaf(y[6], g1, blo(z[0].w)), fmaf(y[7], g1, bhi(z[0].w)));
          }
        } else
#pragma unroll 1
        for (int e = a; e < a + b; e++) {
          const int th = (e & 1) * 64 + w * 8 + rr, pc = e >> 1;
          const uint4* src = g_part + (m * 2 + nh) * MAXP * 4096 + (pc >> 2) * 1024 + hr * 512 + (pc & 3) * 128 + th;
          const int row = m * 128 + hr * 64 + (th >> 5) * 16 + ((th >> 2) & 7) + (mi & 1) * 8;
          uint4 z[8];
#pragma unroll
          for (int i = 0; i < 8; i++) z[i] = 4 * i + mi < p ? __ldcg(src + (4 * i + mi + 1) * 4096) : make_uint4(0, 0, 0, 0);
          const uint32_t zf = __ldcg((const uint32_t*)src + mi);
          const float g = __ldcg(g_gate + row);
          float y[8]; reg_zero<8>(y);
#pragma unroll
          for (int i = 0; i < 8; i++) { y[0] += blo(z[i].x); y[1] += bhi(z[i].x); y[2] += blo(z[i].y); y[3] += bhi(z[i].y); y[4] += blo(z[i].z); y[5] += bhi(z[i].z); y[6] += blo(z[i].w); y[7] += bhi(z[i].w); }
#pragma unroll
          for (int i = 0; i < 4; i++) { const float o = __shfl_xor_sync(0xffffffffu, (mi & 2) ? y[i] : y[i + 4], 16); y[i] = ((mi & 2) ? y[i + 4] : y[i]) + o; }
#pragma unroll
          for (int i = 0; i < 2; i++) { const float o = __shfl_xor_sync(0xffffffffu, (mi & 1) ? y[i] : y[i + 2], 8); y[i] = ((mi & 1) ? y[i + 2] : y[i]) + o; }
          if (!dry) *(uint32_t*)(P.out + row * DM + nh * 256 + pc * 16 + (mi >> 1) * 8 + (th & 3) * 2) = pack(fmaf(y[0], g, blo(zf)), fmaf(y[1], g, bhi(zf)));
        }
      } else if (type == T_AO) {
        float acc[64]; reg_zero<64>(acc);
        const bool sg = w4 >> 1;
#pragma unroll 1
        for (int n = a; n < a + b; n++) {
          uint32_t sl[8], qa[8][4];
          wait_full(); sl[0] = R.sl; R.next();
#pragma unroll
          for (int k = 0; k < 8; k++) ldsm4(qa[k], sb + sl[0] * 16384 + (k >> 2) * 8192 + (frag ^ ((k & 3) * 32)));
          wait_full(); sl[1] = R.sl; R.next();
          float sx[32], sm[8], v[20]; reg_zero<32>(sx); reg_zero<8>(sm);
          wg_fence();
#pragma unroll
          for (int k = 0; k < 8; k++) wg_rs64k(sx, qa[k], desc_k(sb + sl[1] * 16384 + (k >> 2) * 8192) + (k & 3) * 2, k != 0);
          wg_commit(); wg_wait<0>(); reg_fence<32>(sx);
          arrive_p(wb + W_EMPTY + (lane ? sl[1] : sl[0]) * 8, lane < 2);
          const int lim = 16 * (w4 & 1) + gid - 2 * tig;
#pragma unroll
          for (int i = 0; i < 16; i++) v[i] = (8 * (i >> 2) + (i & 1) - 8 * ((i >> 1) & 1) <= lim) ? (sg ? sx[16 + i] : sx[i]) : MASKED;
#pragma unroll
          for (int i = 2; i < 8; i++) { wait_full(); sl[i] = R.sl; R.next(); }
          const uint32_t mb = sb + sl[7] * 16384;
          wg_fence();
#pragma unroll
          for (int k = 0; k < 8; k++) wg_rs16k(sm, qa[k], desc_k(mb + (k >> 2) * 2048) + (k & 3) * 2, k != 0);
          wg_commit(); wg_wait<0>(); reg_fence<8>(sm);
#pragma unroll
          for (int i = 0; i < 4; i++) v[16 + i] = sg ? sm[4 + i] : sm[i];
          uint32_t pa[5][4];
          softmax_p(v, sg, pa);
          float o[64]; reg_zero<64>(o);
          wg_fence();
#pragma unroll
          for (int hf = 0; hf < 2; hf++) {
#pragma unroll
            for (int k = 0; k < 4; k++) wg_rs64(o + 32 * hf, pa[k], desc_mn(sb + sl[2] * 16384 + hf * 8192) + k * 128, k != 0);
            wg_rs64(o + 32 * hf, pa[4], desc_mn(mb + 4096 + hf * 2048), 1);
          }
          wg_commit(); wg_wait<0>(); reg_fence<64>(o);
#pragma unroll
          for (int k = 0; k < 8; k++) { qa[k][0] = pack(o[8 * k], o[8 * k + 1]); qa[k][1] = pack(o[8 * k + 2], o[8 * k + 3]); qa[k][2] = pack(o[8 * k + 4], o[8 * k + 5]); qa[k][3] = pack(o[8 * k + 6], o[8 * k + 7]); }
          wg_fence();
#pragma unroll
          for (int k = 0; k < 8; k++) wg_rs128(acc, qa[k], desc_mn(sb + (wg ? sl[4 + 2 * (k >> 2)] : sl[3 + 2 * (k >> 2)]) * 16384) + (k & 3) * 128, 1);
          wg_commit(); wg_wait<0>(); reg_fence<64>(acc);
          arrive_p(wb + W_EMPTY + ((sl[2] + lane) % NSL) * 8, lane < 6);
        }
        stage_begin();
#pragma unroll
        for (int i = 0; i < 8; i++) { const float* z = acc + 8 * i;
          sts128(stg + i * 2048 + (tid & 127) * 16, pack(z[0], z[1]), pack(z[2], z[3]), pack(z[4], z[5]), pack(z[6], z[7])); }
        stage_end(3 | (2 << 8), ((m * 2 + nh) * MAXP + p) * 4096 + wg * 2048 + hr * 512, 0, F_P2 + (2 * m + hr) * 2 + nh);
      } else {
      while (R.sl % 3) { wait_full(); arrive_e(wb + W_EMPTY + R.sl * 8); R.next(); }
      float acc[128]; reg_zero<128>(acc);
      uint32_t prev = 0;
#pragma unroll 1
      for (int kb = 0; kb < b; kb++) {
        const uint32_t s0 = R.sl;
        wait_full(); R.next(); wait_full(); R.next(); wait_full(); R.next();
        if (SKO && kb == 0 && wg == 1) bar_sync(BAR_SK, 256);
        const uint32_t da = desc_k(sb + s0 * 16384 + wg * 8192), db = desc_mn(sb + s0 * 16384 + 16384);
        wg_fence();
#pragma unroll
        for (int ks = 0; ks < 4; ks++) wg_ss256(acc, da + ks * 2, db + ks * 128, (kb | ks) != 0);
        wg_commit();
        if (SKO && kb == SKO - 1 && wg == 0) bar_arrive(BAR_SK, 256);
        if (kb) { wg_wait<1>(); arrive_p(prev, lane < 3); }
        prev = wb + W_EMPTY + (s0 + lane) * 8;
      }
      wg_wait<0>(); reg_fence<128>(acc);
      arrive_p(prev, lane < 3);
      const uint32_t t16 = (tid & 127) * 16;
      if (type == T_OF) {
        wait_full();
        const float g0 = __ldcg(g_gate + row0 + 16 * w4 + gid), g1 = __ldcg(g_gate + row0 + 16 * w4 + gid + 8);
        for (int i = p; i >= 0; i--) {
          const float a0 = i ? 1.f : g0, a1 = i ? 1.f : g1;
#pragma unroll
          for (int q = 0; q < 4; q++) {
            wait_full();
            uint32_t dep = 0;
#pragma unroll
            for (int k = 0; k < 4; k++) {
              uint32_t z[4]; lds128(z, sb + R.sl * 16384 + wg * 8192 + k * 2048 + t16);
              float* y = acc + 32 * q + 8 * k;
              y[0] = fmaf(y[0], a0, blo(z[0])); y[1] = fmaf(y[1], a0, bhi(z[0])); y[2] = fmaf(y[2], a1, blo(z[1])); y[3] = fmaf(y[3], a1, bhi(z[1]));
              y[4] = fmaf(y[4], a0, blo(z[2])); y[5] = fmaf(y[5], a0, bhi(z[2])); y[6] = fmaf(y[6], a1, blo(z[3])); y[7] = fmaf(y[7], a1, bhi(z[3]));
              dep ^= z[0];
            }
            arrive_e(wb + W_EMPTY + R.sl * 8 + (dep & zero));
            R.next();
          }
        }
      } else if (a >= 64) {
        const float g0 = 1.f - __ldcg(g_gate + row0 + 16 * w4 + gid), g1 = 1.f - __ldcg(g_gate + row0 + 16 * w4 + gid + 8);
#pragma unroll
        for (int i = 0; i < 128; i++) acc[i] *= (i & 2) ? g1 : g0;
      }
      uint32_t xs = R.sl;
      wait_full(); R.next();
      wait_full();
      arrive_e(wb + W_EMPTY + (wg ? xs : R.sl) * 8);
      if (wg) xs = R.sl;
      R.next();
      stage_begin();
#pragma unroll
      for (int i = 0; i < 16; i++) { const float* z = acc + 8 * i;
        const uint32_t base = i < 8 ? stg : sb + xs * 16384, z0 = pack(z[0], z[1]), z1 = pack(z[2], z[3]), z2 = pack(z[4], z[5]), z3 = pack(z[6], z[7]);
        if (type == T_OP) sts128(base + (i & 7) * 2048 + t16, z0, z1, z2, z3);
        else stsm4(base + ((i >> 2) & 1) * 8192 + (frag ^ ((i & 3) * 32)), z0, z1, z2, z3); }
      if (type == T_OP) stage_end(3 | (4 << 8) | (xs << 16), ((m * 2 + nh) * MAXP + p) * 4096 + wg * 512, 0, F_P + m * 2 + nh);
      else stage_end(2 | (4 << 8) | (xs << 16), nh * 256, row0, 0xFFFFFFFFu);
      }
    } else {
      uint32_t xa[32][4];
      { uint32_t pv = 0;
        if (wg) { arrive_e(wb + W_EMPTY + R.sl * 8); R.skip(4); }
#pragma unroll
        for (int k2 = 0; k2 < 4; k2++) {
          wait_full();
#pragma unroll
          for (int ks = 0; ks < 8; ks++) ldsm4(xa[k2 * 8 + ks], sb + R.sl * 16384 + (ks >> 2) * 8192 + (frag ^ ((ks & 3) * 32)));
          if (k2) { uint32_t d = 0;
#pragma unroll
            for (int ks = 0; ks < 8; ks++) d ^= xa[k2 * 8 - 8 + ks][0];
            arrive_p(pv + (d & zero), lane < (k2 == 1 ? 1 + wg : 2)); }
          pv = wb + W_EMPTY + R.sl * 8;
          R.next();
        }
        uint32_t d = 0;
#pragma unroll
        for (int ks = 0; ks < 8; ks++) d ^= xa[24 + ks][0];
        arrive_p(pv + (d & zero), lane < 2);
        if (!wg) R.skip(4);
      }
      const int skew = type == T_QA ? SKQ : type == T_F ? SKF : SKEW;
      for (int n = a; n < a + b; n++) {
        float acc[64]; reg_zero<64>(acc);
        uint32_t prev = 0;
        const bool sk = (n == a || SKA) && R.fl;
#pragma unroll
        for (int kb = 0; kb < 8; kb++) {
          wait_full();
          if (kb == 0 && sk && wg == 1) bar_sync(BAR_SK, 256);
          const uint32_t db = desc_mn(sb + R.sl * 16384);
          wg_fence();
#pragma unroll
          for (int ks = 0; ks < 4; ks++) wg_rs128(acc, xa[kb * 4 + ks], db + ks * 128, (kb | ks) != 0);
          wg_commit();
          if (kb == (n == a && SK1 ? SK1 : skew) - 1 && sk && wg == 0) bar_arrive(BAR_SK, 256);
          if (kb) { wg_wait<1>(); arrive_e(prev); }
          prev = wb + W_EMPTY + R.sl * 8;
          R.next();
        }
        wg_wait<0>(); reg_fence<64>(acc);
        arrive_e(prev);
        if (type == T_QA) {
          uint32_t qa[8][4];
#pragma unroll
          for (int k = 7; k >= 0; k--) { qa[k][0] = pack(acc[8 * k], acc[8 * k + 1]); qa[k][1] = pack(acc[8 * k + 2], acc[8 * k + 3]); qa[k][2] = pack(acc[8 * k + 4], acc[8 * k + 5]); qa[k][3] = pack(acc[8 * k + 6], acc[8 * k + 7]); }
          if (wg) R.skip(3);
          uint32_t sl[3];
          const bool sg = w4 >> 1;
          const int lim = 16 * (w4 & 1) + gid - 2 * tig;
          float v[20];
#pragma unroll
          for (int i = 0; i < 2; i++) { wait_full(); sl[i] = R.sl; R.next(); }
          const uint32_t mb = sb + sl[1] * 16384;
          { float sx[32], sm[8]; reg_zero<32>(sx); reg_zero<8>(sm);
            wg_fence();
#pragma unroll
            for (int k = 7; k >= 0; k--) wg_rs64k(sx, qa[k], desc_k(sb + sl[0] * 16384 + (k >> 2) * 8192) + (k & 3) * 2, k != 7);
#pragma unroll
            for (int k = 7; k >= 0; k--) wg_rs16k(sm, qa[k], desc_k(mb + (k >> 2) * 2048) + (k & 3) * 2, k != 7);
            wg_commit();
            stage_begin();
            wg_wait<0>(); reg_fence<32>(sx); reg_fence<8>(sm);
            arrive_p(wb + W_EMPTY + sl[0] * 8, lane < 2);
#pragma unroll
            for (int i = 0; i < 16; i++) v[i] = (8 * (i >> 2) + (i & 1) - 8 * ((i >> 1) & 1) <= lim) ? (sg ? sx[16 + i] : sx[i]) : MASKED;
#pragma unroll
            for (int i = 0; i < 4; i++) v[16 + i] = sg ? sm[4 + i] : sm[i];
          }
          uint32_t pa[5][4];
          softmax_p(v, sg, pa);
          wait_full(); sl[2] = R.sl; R.next();
#pragma unroll
          for (int hf = 0; hf < 2; hf++) {
            float o[32]; reg_zero<32>(o);
            wg_fence();
#pragma unroll
            for (int k = 0; k < 4; k++) wg_rs64(o, pa[k], desc_mn(sb + sl[2] * 16384 + hf * 8192) + k * 128, k != 0);
            wg_rs64(o, pa[4], desc_mn(mb + 4096 + hf * 2048), 1);
            wg_commit(); wg_wait<0>(); reg_fence<32>(o);
            if (hf) arrive2_p(wb + W_EMPTY + (lane ? sl[2] : sl[1]) * 8, lane < 2);
#pragma unroll
            for (int jj = 0; jj < 4; jj++)
              stsm4(stg + hf * 8192 + (frag ^ (jj * 32)), pack(o[8 * jj], o[8 * jj + 1]), pack(o[8 * jj + 2], o[8 * jj + 3]), pack(o[8 * jj + 4], o[8 * jj + 5]), pack(o[8 * jj + 6], o[8 * jj + 7]));
          }
          stage_end(1 | (2 << 8), n * 128, row0, F_O + m * 32 + n);
          if (!wg) R.skip(3);
        } else if (type == T_F) {
#pragma unroll
          for (int i = 0; i < 32; i++) acc[i] = acc[i] * rcpa(1.f + ex2(-1.4426950408889634f * acc[i])) * acc[i + 32];
          stage_begin();
#pragma unroll
          for (int jj = 0; jj < 4; jj++)
            stsm4(stg + (frag ^ (jj * 32)), pack(acc[8 * jj], acc[8 * jj + 1]), pack(acc[8 * jj + 2], acc[8 * jj + 3]), pack(acc[8 * jj + 4], acc[8 * jj + 5]), pack(acc[8 * jj + 6], acc[8 * jj + 7]));
          stage_end(1 | (1 << 8), 4096 + n * 64, row0, F_H + m);
        } else {
          stage_begin();
#pragma unroll
          for (int jj = 0; jj < 8; jj++)
            stsm4(stg + (jj >> 2) * 8192 + (frag ^ ((jj & 3) * 32)), pack(acc[8 * jj], acc[8 * jj + 1]), pack(acc[8 * jj + 2], acc[8 * jj + 3]), pack(acc[8 * jj + 4], acc[8 * jj + 5]), pack(acc[8 * jj + 6], acc[8 * jj + 7]));
          if (n < 64) stage_end(0 | (2 << 8), (n & 1) * 4096 + (n >> 1) * 128, row0, F_KV + (2 * m + wg) * 32 + (n >> 1));
          else stage_end(1 | (2 << 8), (n - 64) * 128, row0, F_O + m * 32 + n - 64);
        }
      }
      if (type == T_F && a == 0) {
        const uint32_t* gw = (const uint32_t*)P.gate_w + tig;
        uint32_t u[64];
#pragma unroll
        for (int k = 0; k < 64; k++) u[k] = __ldg(gw + k * 4);
        float c0[4], c1[4];
        mmaz(c0, xa[0], u[0], u[1]); mmaz(c1, xa[1], u[2], u[3]);
#pragma unroll
        for (int k = 2; k < 32; k += 2) { mma(c0, xa[k], u[2 * k], u[2 * k + 1]); mma(c1, xa[k + 1], u[2 * k + 2], u[2 * k + 3]); }
        const float z = (tig & 1) ? c0[2] + c1[2] : c0[0] + c1[0];
        stage_begin();
        sts32(stg + (16 * w4 + gid + (tig & 1) * 8) * 4, __float_as_uint(rcpa(1.f + ex2(-1.4426950408889634f * z))));
        stage_end(4 | (1 << 8), row0, 0, F_H + m);
      }
    }
    if (dry) return;
  }
  stage_begin();
  stage_end(T_EXIT, 0, 0, 0);
}

__global__ void __launch_bounds__(384, 1) fused_kernel(const __grid_constant__ Params P) {
  extern __shared__ uint8_t smem_raw[];
  const uint32_t sb = (smem_u32(smem_raw) + 1023) & ~1023u;
  asm volatile("griddepcontrol.launch_dependents;");
  if (threadIdx.x < 32) TP(0);
  uint32_t r; asm("mov.u32 %0, %%cluster_ctarank;" : "=r"(r));
  const int w = __shfl_sync(0xffffffffu, threadIdx.x >> 5, 0);
  const uint32_t bar = sb + O_BAR, wb = sb + O_WB;
  auto l2_prefetch = [&]() {
    const int id = blockIdx.x + 112 * (threadIdx.x & 31);
    if (P.isA && id < PFN) {
      const char* p = id < 16 ? P.pf[0] + id * 16384 : id < 528 ? P.pf[1 + (id & 1)] + ((id - 16) >> 1) * 16384 : P.pf[3 + ((id - 528) >> 8)] + ((id - 528) & 255) * 16384;
      asm volatile("cp.async.bulk.prefetch.L2.global [%0], 16384;" :: "l"(p) : "memory");
    }
    __syncwarp();
  };
  if (w >= 8) {
    if ((threadIdx.x & 31) == 0) {
      if (w == 8) {
#pragma unroll
        for (int i = 0; i < (int)NSL; i++) mbar_init(wb + W_FULL + i * 8, 1);
      } else if (w == 9) {
#pragma unroll
        for (int i = 0; i < (int)NSL; i++) mbar_init(wb + W_EMPTY + i * 8, 8);
      } else if (w == 10) {
        mbar_init(wb + W_STF, 4); mbar_init(wb + W_STF + 8, 4); mbar_init(wb + W_STE, 1); mbar_init(wb + W_STE + 8, 1); mbar_init(wb + W_DONE, 3); mbar_init(wb + W_REQ, 1); mbar_init(wb + W_RES, 1);
#pragma unroll
        for (int i = 0; i < 2 * NG; i++) mbar_init(bar + i * 8, bar_cnt(i));
#pragma unroll
        for (int i = 0; i < 2 * NG; i++) mbar_expect(bar + i * 8, bar_tx(i));
      } else {
        mbar_init(bar + B_SC, 1); mbar_init(bar + B_V, 8); mbar_init(bar + B_RS, 1); mbar_init(bar + B_RS + 8, 1); mbar_init(bar + B_ROLE, 1);
#pragma unroll
        for (int i = 0; i < 4; i++) { mbar_init(bar + B_KV + i * 8, 1); mbar_init(bar + B_I0 + i * 8, 1); }
        mbar_expect(bar + B_ROLE, 4);
      }
      asm volatile("fence.mbarrier_init.release.cluster;" ::: "memory");
    }
    __syncwarp();
    if (w == 10) TP(12);
  } else if (DRY && (w == 2 || w == 3)) {
    if ((threadIdx.x & 31) == 0) {
#pragma unroll
      for (int i = 0; i < 14; i++) mbar_init(wb + W_DRY + (w - 2) * 112 + i * 8, 1000);
      sts64(wb + W_DRY + W_INFO, 1u << 14, (1u << 14) | ((r & 1) ? T_AO : T_RD | (1u << 29))); sts64(wb + W_DRY + W_DESC + 64, 1022, 1022);
    }
    __syncwarp();
  } else if (w == 5) {
    if (PFM == 1) l2_prefetch();
    if (!P.isA && blockIdx.x == 0) { const int i = threadIdx.x & 31;
      asm volatile("prefetch.global.L2 [%0];" :: "l"(g_tasks + min(i * 32, (int)NTASK - 1)));
     asm volatile("prefetch.global.L2 [%0];" :: "l"(g_grp + (i & 3) * 32)); }
  } else if (w == 4) {
    if (TMP && (threadIdx.x & 31) < 20) asm volatile("prefetch.param.tensormap [%0];" :: "l"(__cvta_generic_to_grid_constant(&P.wq + (threadIdx.x & 31))) : "memory");
    __syncwarp();
    TP(13);
  }
  asm volatile("barrier.cluster.arrive.relaxed.aligned;" ::: "memory");
  uint32_t role = 0;
  if (r == 0 && w < 2) {
    uint32_t* p = (uint32_t*)(win_base() + 262144) + w * 1024 + (P.isA ? blockIdx.x >> 4 : 8 + blockIdx.x) * 32;
    p[threadIdx.x & 31] = 0;
    __syncwarp();
    if ((threadIdx.x & 31) == 0) {
      uint32_t best = 0xFFFFFFFFu, v = 0;
#pragma unroll 1
      for (int i = 0; i < NPR; i++) {
        const uint32_t t0 = clk() + v;
        asm volatile("atom.relaxed.gpu.global.exch.b32 %0, [%1], 0;" : "=r"(v) : "l"(p + v) : "memory");
        v &= P.zero;
        sts32(wb + W_ROLE + 8, v);
        best = min(best, clk() - t0);
      }
      sts32(wb + W_ROLE + 16 + w * 4, best);
    }
    __syncwarp();
    if (w == 1) TP(14);
    bar_sync(BAR_E, 64);
    if (threadIdx.x == 0) {
      uint32_t x, y; lds64(x, y, wb + W_ROLE + 16);
      const uint32_t sd = (P.cmap & 1) ? 0 : x > y;
      uint32_t v = 0, idx = 9;
      if (P.isA) { v = atomicAdd(&g_tk, sd ? 0x100 : 1); idx = (v >> (sd * 8)) & 255; v += sd ? 0x100 : 1; }
      for (uint32_t n = 0; (v & 255) < 4 && (v >> 8) < 4; n++) { asm volatile("ld.relaxed.gpu.global.u32 %0, [%1];" : "=r"(v) : "l"(&g_tk) : "memory"); if (n > (1u << 22)) *(volatile uint32_t*)8 = 0; }
      const bool major = ((v >> (sd * 8)) & 255) >= 4;
      role = (major && idx < 4 ? idx : 9) | ((major ? sd : sd ^ 1) << 8) | (major << 9);
    }
    __syncwarp();
  }
  asm volatile("barrier.cluster.wait.aligned;" ::: "memory");
  if (r == 0 && w == 0) {
    role = __shfl_sync(0xffffffffu, role, 0);
    if (threadIdx.x < (P.isA ? 16 : 2)) st_async1(mapa(wb + W_ROLE, threadIdx.x), mapa(bar + B_ROLE, threadIdx.x), role);
    __syncwarp();
  }
  if (w == 5) TP(15);
  auto get_role = [&]() { mbar_spin(bar + B_ROLE, 0); return __shfl_sync(0xffffffffu, lds32(wb + W_ROLE), 0); };
  if (w < 8) {
    const int wdry = DRY == 2 ? __shfl_sync(0xffffffffu, r ? 0 : 4, 0) : 4;
    asm volatile("setmaxnreg.inc.sync.aligned.u32 232;");
#pragma unroll 1
    for (int pass = 0;; pass++) {
      const uint32_t zp = pass & P.zero;
      if (pass || (DRY && w >= wdry)) consumer(P, sb | zp, w | zp, threadIdx.x | zp, !pass);
      if (pass) break;
      if (w == 4) TP(1);
      const int ro = get_role(), c = ro & 255;
      if (c < 4) {
        bar_sync(BAR_SK + 2 + (w >> 2), 128);
        asm volatile("setmaxnreg.dec.sync.aligned.u32 %0;" :: "n"(RG));
        const uint32_t zc = c & P.zero, rc = r | zc;
        chain_gemm(P, sb | zc, rc, c, 8 * c + (rc >> 1), rc & 1, w | zc, (ro >> 8) & 1);
        bar_sync(BAR_G, 256);
        asm volatile("setmaxnreg.inc.sync.aligned.u32 232;");
      }
    }
  } else {
    asm volatile("setmaxnreg.dec.sync.aligned.u32 40;");
    const int u = w - 8;
    int c = get_role();
    const int side = (c >> 8) & 1; c &= 255;
    if (u == 0) TP(2);
    if (c < 4) {
      const int h = 8 * c + (r >> 1), j = r & 1;
      if (u == 0) {
        for (int i = 0; i < 2; i++) {
          arrive_tx_e(bar + B_I0 + i * 8, 65536);
          const CUtensorMap* mp = i == 0 ? &P.wkc : &P.wvc;
          const uint32_t d = sb + (i == 0 ? O_BUF2 : O_BUF0);
          tma4d(d, mp, bar + B_I0 + i * 8, h * 128 + j * 64, 0); tma4d(d + 32768, mp, bar + B_I0 + i * 8, h * 128 + j * 64, 16);
        }
        arrive_tx_e(bar + B_I0 + 16, 65536);
        for (int b = 0; b < 4; b++) tma3d(sb + O_BUF1 + b * 16384, &P.wo, bar + B_I0 + 16, h * 128 + (b & 1) * 64, j * 4 + (b >> 1) * 2);
        if (QPF) for (int b = 0; b < 2; b++)
          asm volatile("{\n.reg .pred q;\nelect.sync _|q, 0xffffffff;\n@q cp.async.bulk.prefetch.tensor.4d.L2.global [%0, {%1, %2, %2, %3}];\n}" :: "l"(&P.wqc), "r"(h * 128 + j * 64), "r"(0), "r"(b * 16) : "memory");
      }
      const int lane = threadIdx.x & 31;
      const unsigned short* mp = (const unsigned short*)P.mem0 + (lane >> 2) * DM + 32 * r + 16 * (u >> 1) + 4 * (u & 1) + (lane & 3);
      const uint32_t word = (uint32_t)mp[0] | ((uint32_t)mp[8] << 16);
      if (NEX && u == 0) { sts64(wb + W_NEXT, g_tasks[NEX + c * 16 + r], (NEX + c * 16 + r) | 0x80000000u); arrive_e(wb + W_RES); }
      bar_sync(BAR_S, 128);
      asm volatile("setmaxnreg.inc.sync.aligned.u32 %0;" :: "n"(504 - 2 * RG));
      if (u < 2) chain_comm<true>(P, sb, r, c, h, j, u, side, word); else chain_comm<false>(P, sb, r, c, h, j, u, side, word);
      fence_async_smem(); bar_sync(BAR_O, 384);
      asm volatile("setmaxnreg.dec.sync.aligned.u32 40;");
    }
    const int ro = get_role();
    uint32_t* const fl = flags_base((ro >> 8) & 1);
    if (u < 3) {
      if (u == 0) producer(P, sb, fl); else storer(P, sb, fl, u - 1);
      arrive_e(wb + W_DONE);
    } else claimer(P, sb, fl, (ro & 255) < 4, ro >> 9);
  }
}

typedef CUresult (*EncFn)(CUtensorMap*, CUtensorMapDataType, cuuint32_t, void*, const cuuint64_t*, const cuuint64_t*, const cuuint32_t*, const cuuint32_t*,
                          CUtensorMapInterleave, CUtensorMapSwizzle, CUtensorMapL2promotion, CUtensorMapFloatOOBfill);
static void map2d(EncFn f, CUtensorMap* m, const void* p, uint64_t cols, uint64_t rows, uint32_t br, uint32_t bc = 64) {
  cuuint64_t d[2] = {cols, rows}, st[1] = {cols * 2}; cuuint32_t b[2] = {bc, br}, e[2] = {1, 1};
  f(m, CU_TENSOR_MAP_DATA_TYPE_BFLOAT16, 2, (void*)p, d, st, b, e, CU_TENSOR_MAP_INTERLEAVE_NONE, bc == 64 ? CU_TENSOR_MAP_SWIZZLE_128B : CU_TENSOR_MAP_SWIZZLE_NONE, CU_TENSOR_MAP_L2_PROMOTION_L2_256B, CU_TENSOR_MAP_FLOAT_OOB_FILL_NONE);
}
static void map3d(EncFn f, CUtensorMap* m, const void* p, uint64_t cols, uint64_t rows) {
  cuuint64_t d[3] = {64, rows, cols / 64}, st[2] = {cols * 2, 128}; cuuint32_t b[3] = {64, 64, 2}, e[3] = {1, 1, 1};
  f(m, CU_TENSOR_MAP_DATA_TYPE_BFLOAT16, 3, (void*)p, d, st, b, e, CU_TENSOR_MAP_INTERLEAVE_NONE, CU_TENSOR_MAP_SWIZZLE_128B, CU_TENSOR_MAP_L2_PROMOTION_L2_256B, CU_TENSOR_MAP_FLOAT_OOB_FILL_NONE);
}

static void map4d(EncFn f, CUtensorMap* m, const void* p) {
  cuuint64_t d[4] = {4096, 2, 8, 32}, st[3] = {8 * 8192, 8192, 16 * 8192}; cuuint32_t b[4] = {64, 2, 8, 16}, e[4] = {1, 1, 1, 1};
  f(m, CU_TENSOR_MAP_DATA_TYPE_BFLOAT16, 4, (void*)p, d, st, b, e, CU_TENSOR_MAP_INTERLEAVE_NONE, CU_TENSOR_MAP_SWIZZLE_128B, CU_TENSOR_MAP_L2_PROMOTION_L2_128B, CU_TENSOR_MAP_FLOAT_OOB_FILL_NONE);
}
static void map4k(EncFn f, CUtensorMap* m, const void* p) {
  cuuint64_t d[4] = {8192, 8, 2, S / 16}, st[3] = {2 * 16384, 16384, 16 * 16384}; cuuint32_t b[4] = {64, 8, 2, 2}, e[4] = {1, 1, 1, 1};
  f(m, CU_TENSOR_MAP_DATA_TYPE_BFLOAT16, 4, (void*)p, d, st, b, e, CU_TENSOR_MAP_INTERLEAVE_NONE, CU_TENSOR_MAP_SWIZZLE_128B, CU_TENSOR_MAP_L2_PROMOTION_L2_128B, CU_TENSOR_MAP_FLOAT_OOB_FILL_NONE);
}
static uint32_t h_cmap = 0;
extern "C" void kernel_launch(void* const* d_in, const int* in_sizes, int n_in, void* d_out, int out_size) {
  void* fn = nullptr; cudaDriverEntryPointQueryResult qr;
  cudaGetDriverEntryPoint("cuTensorMapEncodeTiled", &fn, cudaEnableDefault, &qr);
  EncFn f = (EncFn)fn;
  void *kv, *oh, *kvm;
  cudaGetSymbolAddress(&kv, g_kv); cudaGetSymbolAddress(&oh, g_oh); cudaGetSymbolAddress(&kvm, g_kvm);
  Params P;
  map3d(f, &P.wq, d_in[2], 4096, 512); map3d(f, &P.wk, d_in[3], 4096, 512); map3d(f, &P.wv, d_in[4], 4096, 512);
  map4d(f, &P.wqc, d_in[2]); map4d(f, &P.wkc, d_in[3]); map4d(f, &P.wvc, d_in[4]);
  map3d(f, &P.wo, d_in[5], 512, 4096); map3d(f, &P.wd, d_in[10], 512, 1376);
  map2d(f, &P.wg, d_in[8], 1376, 512, 64); map2d(f, &P.wu, d_in[9], 1376, 512, 64);
  map3d(f, &P.x, d_in[0], 512, S); map2d(f, &P.kvl, kv, 8192, S, 128); map2d(f, &P.ohl, oh, OHW, S, 128);
  map2d(f, &P.kvc, kv, 8192, S, 32); map2d(f, &P.kvm, kvm, 8192, NSEG * 8, 16); map2d(f, &P.kvx, kvm, 8192, NSEG * 8, 8); map4k(f, &P.kp, kv);
  map2d(f, &P.st[0], kv, 8192, S, 64); map2d(f, &P.st[1], oh, OHW, S, 64); map2d(f, &P.st[2], d_out, 512, S, 64);
  P.mem0 = (const bf16*)d_in[1]; P.gate_w = (const bf16*)d_in[11]; P.zero = 0; P.out = (bf16*)d_out;
  P.pf[0] = (const char*)d_in[0]; P.pf[1] = (const char*)d_in[3]; P.pf[2] = (const char*)d_in[4]; P.pf[3] = (const char*)d_in[2]; P.pf[4] = (const char*)d_in[5];
  P.cmap = h_cmap;
  cudaFuncSetAttribute(fused_kernel, cudaFuncAttributeNonPortableClusterSizeAllowed, 1);
  cudaFuncSetAttribute(fused_kernel, cudaFuncAttributeMaxDynamicSharedMemorySize, SMEM_BYTES);
  cudaLaunchConfig_t cfg = {};
  cfg.blockDim = dim3(384); cfg.dynamicSmemBytes = SMEM_BYTES; cfg.stream = cudaStreamPerThread;
  cudaLaunchAttribute at[2];
  cfg.attrs = at; cfg.numAttrs = 1;
  cfg.gridDim = dim3(112);
  at[0].id = cudaLaunchAttributeClusterDimension; at[0].val.clusterDim.x = 16; at[0].val.clusterDim.y = 1; at[0].val.clusterDim.z = 1;
  P.isA = 1;
  cudaLaunchKernelEx(&cfg, fused_kernel, P);
  cfg.gridDim = dim3(20);
  at[0].val.clusterDim.x = 2;
  at[1].id = cudaLaunchAttributeProgrammaticStreamSerialization; at[1].val.programmaticStreamSerializationAllowed = 1;
  cfg.numAttrs = 2;
  P.isA = 0;
  cudaLaunchKernelEx(&cfg, fused_kernel, P);
}
```
